```python
import torch

def _softmax(x, axis=-1):
    return torch.softmax(x, dim=axis)
def _gelu(x):
    return torch.nn.functional.gelu(x, approximate="tanh")
def _silu(x):
    return torch.nn.functional.silu(x)
def _sigmoid(x):
    return torch.sigmoid(x)
def _layernorm(x, axis=-1, eps=1e-5):
    m = x.mean(dim=axis, keepdim=True)
    v = x.var(dim=axis, keepdim=True, unbiased=False)
    return (x - m) / torch.sqrt(v + eps)
def _scatter_add(tgt, idx, src, axis=0):
    return tgt.clone().index_add_(axis, idx, src)
def _segment_sum(src, seg, n):
    out = torch.zeros((n,) + src.shape[1:], dtype=src.dtype)
    return out.index_add_(0, seg, src)
def _pad(x, pw):
    flat = tuple(v for pair in reversed(pw) for v in pair)
    return torch.nn.functional.pad(x, flat)

kernel_name = 'parallel_sum__mha_block__moe_arch_mod__prompt'

def setup_inputs():

    _w = (lambda a: (lambda t: t.to(torch.bfloat16) if t.is_floating_point() else t)(torch.as_tensor(a)))
    def _A_setup():
        B, S, D, H = 1, 2048, 512, 32
        return {
            "x": _w((lambda *s: torch.randn(*s, dtype=torch.bfloat16) * 0.05)(B, S, D)),
            "wqkv": _w((lambda *s: torch.randn(*s, dtype=torch.bfloat16) * 0.2)(D, 3 * D)),
            "wo": _w((lambda *s: torch.randn(*s, dtype=torch.bfloat16) * 0.1)(D, D)),
        }
    _A_in = _A_setup()

    def _B_setup():
        B, S, D, F, C = 1, 2048, 512, 1792, 1
        return {
            "x": _w((lambda *s: torch.randn(*s, dtype=torch.bfloat16) * 0.05)(B, S, D)),
            "w_r": _w((lambda *s: torch.randn(*s, dtype=torch.bfloat16) * 1.6)(D)),
            "w_gate": _w((lambda *s: torch.randn(*s, dtype=torch.bfloat16) * 0.2)(D, F)),
            "w_up": _w((lambda *s: torch.randn(*s, dtype=torch.bfloat16) * 0.2)(D, F)),
            "w_down": _w((lambda *s: torch.randn(*s, dtype=torch.bfloat16) * 0.2)(F, D)),
        }
    _B_in = _B_setup()

    return {
        "A_x": _A_in["x"],
        "A_wqkv": _A_in["wqkv"],
        "A_wo": _A_in["wo"],
        "B_x": _B_in["x"],
        "B_w_r": _B_in["w_r"],
        "B_w_gate": _B_in["w_gate"],
        "B_w_up": _B_in["w_up"],
        "B_w_down": _B_in["w_down"],
    }

def reference(A_x, A_wqkv, A_wo, B_x, B_w_r, B_w_gate, B_w_up, B_w_down):
    def _A_ref(x, wqkv, wo):
        B, S, D = x.shape
        H = 32
        Dh = D // H
        qkv = (lambda x, *d: x.permute(*d))((x @ wqkv).reshape(B, S, 3, H, Dh), 2, 0, 3, 1, 4)
        q, k, v = qkv[0], qkv[1], qkv[2]
        scores = torch.einsum("bhqd,bhkd->bhqk", q, k) * (Dh ** -0.5)
        p = _softmax(scores, axis=-1)
        o = torch.einsum("bhqk,bhkd->bhqd", p, v)
        return (lambda x, *d: x.permute(*d))(o, 0, 2, 1, 3).reshape(B, S, D) @ wo

    def _B_ref(x, w_r, w_gate, w_up, w_down):
        B, S, D = x.shape
        C = 1
        r = x @ w_r
        idx = torch.argsort(-r, axis=-1)[:, :C]
        idx_e = (lambda x, n, axis: torch.repeat_interleave(x, n, dim=axis))(idx.reshape(B, C, 1), D, axis=2)
        x_sel = (lambda x, i, axis: torch.take_along_dim(x, i, dim=axis))(x, idx_e, axis=1)
        g = _silu(x_sel @ w_gate)
        u = x_sel @ w_up
        y = (g * u) @ w_down
        r_sel = _sigmoid((lambda x, i, axis: torch.take_along_dim(x, i, dim=axis))(r, idx, axis=1))
        y = y * r_sel.reshape(B, C, 1)
        b_off = (torch.arange(B) * S).reshape(B, 1)
        flat_idx = (idx + b_off).reshape(B * C)
        zero = (x * 0.0).reshape(B * S, D)
        upd = _scatter_add(zero, flat_idx, y.reshape(B * C, D), axis=0)
        return x + upd.reshape(B, S, D)

    x = A_x
    xn = _layernorm(x, axis=-1)
    return x + _A_ref(xn, A_wqkv, A_wo) + _B_ref(xn, B_w_r, B_w_gate, B_w_up, B_w_down)
```

```cpp
#include <cuda_runtime.h>
#include <cuda_bf16.h>
#include <cuda.h>
#include <stdint.h>

namespace {

constexpr int NCTA = 132;
constexpr uint32_t A_STAGE = 40960, A_WOFF = 16384;
constexpr uint32_t R_SLOT = 10240, R_STREAM = 40960;
constexpr uint32_t SM_OG0 = 81920, SM_WO = 147456, SM_OG1 = 0;
constexpr uint32_t SM_AUG = 212992, SM_BAR = 213760, SM_MISC = 214016, SM_TOTAL = 214272;
constexpr uint32_t B_FULLA = 0, B_EMPTYA = 40, B_FULLR = 64, B_EMPTYR = 128, B_WO = 192, B_OG0 = 200, B_OG1 = 208;
constexpr int SPIN_LIMIT = 1 << 22;
constexpr float M_MARGIN = 90.0f;

__device__ __align__(1024) uint8_t g_xn[2048 * 1024];
__device__ __align__(1024) uint8_t g_kv[32 * 16 * 8192];
__device__ __align__(1024) uint8_t g_o[16 * 2 * 16 * 4096];
__device__ uint32_t g_qscr[128 * 4 * 512];
__device__ float g_y[4 * 512];
__device__ unsigned long long g_best;
__device__ unsigned g_start;
__device__ unsigned g_ffn;
__device__ unsigned g_ln[16 * 32];
__device__ unsigned g_kvf[8 * 32];
__device__ unsigned g_of[32 * 32];

#define PIN_F(x) asm volatile("" : "+f"(x) :: "memory")
#define PIN_R(x) asm volatile("" : "+r"(x) :: "memory")
#define DESC_ADD(d, n) asm volatile("add.s64 %0, %0, " #n ";" : "+l"(d))

__device__ __forceinline__ void wg_fence() { asm volatile("wgmma.fence.sync.aligned;" ::: "memory"); }
__device__ __forceinline__ void wg_commit() { asm volatile("wgmma.commit_group.sync.aligned;" ::: "memory"); }
template <int N> __device__ __forceinline__ void wg_wait() { asm volatile("wgmma.wait_group.sync.aligned %0;" :: "n"(N) : "memory"); }
__device__ __forceinline__ uint64_t mkdesc(uint32_t a, uint32_t lbo, uint32_t sbo, uint32_t swz) {
  return (uint64_t)((a & 0x3FFFF) >> 4) | ((uint64_t)(lbo >> 4) << 16) | ((uint64_t)(sbo >> 4) << 32) | ((uint64_t)swz << 62);
}
__device__ __forceinline__ void mbar_init(uint32_t a, uint32_t c) { asm volatile("mbarrier.init.shared::cta.b64 [%0], %1;" :: "r"(a), "r"(c) : "memory"); }
__device__ __forceinline__ void mbar_expect(uint32_t a, uint32_t b) { asm volatile("mbarrier.arrive.expect_tx.shared::cta.b64 _, [%0], %1;" :: "r"(a), "r"(b) : "memory"); }
__device__ __forceinline__ void mbar_arrive(uint32_t a) { asm volatile("mbarrier.arrive.shared::cta.b64 _, [%0];" :: "r"(a) : "memory"); }
__device__ __forceinline__ void mbar_wait(uint32_t a, uint32_t ph) {
  asm volatile("{\n.reg .pred p;\n.reg .u32 n;\nmov.u32 n, 0;\n"
               "W: mbarrier.try_wait.parity.shared::cta.b64 p, [%0], %1;\nvote.sync.all.pred p, p, 0xffffffff;\n@p bra.uni D;\n"
               "add.u32 n, n, 1;\nsetp.lt.u32 p, n, 0x400000;\n@p bra.uni W;\ntrap;\nD:\n}" :: "r"(a), "r"(ph) : "memory");
}
__device__ __forceinline__ void wait_flag_warp(const unsigned* p, unsigned target) {
  asm volatile("{\n.reg .pred p;\n.reg .u32 n, v;\nmov.u32 n, 0;\n"
               "W: ld.relaxed.gpu.global.u32 v, [%0];\nsub.s32 v, v, %1;\nsetp.ge.s32 p, v, 0;\nvote.sync.all.pred p, p, 0xffffffff;\n@p bra.uni D;\n"
               "add.u32 n, n, 1;\nsetp.lt.u32 p, n, 0x400000;\n@p bra.uni W;\ntrap;\n"
               "D: fence.acq_rel.gpu;\nfence.proxy.async;\n}" :: "l"(p), "r"(target) : "memory");
}
__device__ __forceinline__ void elect_load(uint32_t dst, const void* src, uint32_t bytes, uint32_t bar, uint32_t expect) {
  asm volatile("{\n.reg .pred p, q;\nelect.sync _|p, 0xffffffff;\nsetp.ne.and.u32 q, %4, 0, p;\n"
               "@q mbarrier.arrive.expect_tx.shared::cta.b64 _, [%3], %4;\n"
               "@p cp.async.bulk.shared::cluster.global.mbarrier::complete_tx::bytes [%0], [%1], %2, [%3];\n}"
               :: "r"(dst), "l"(src), "r"(bytes), "r"(bar), "r"(expect) : "memory");
}
__device__ __forceinline__ void elect_tma4d(uint32_t dst, const CUtensorMap* m, int c1, int c3, uint32_t bar, uint32_t expect) {
  asm volatile("{\n.reg .pred p;\nelect.sync _|p, 0xffffffff;\n"
               "@p mbarrier.arrive.expect_tx.shared::cta.b64 _, [%4], %5;\n"
               "@p cp.async.bulk.tensor.4d.shared::cluster.global.mbarrier::complete_tx::bytes [%0], [%1, {0, %2, 0, %3}], [%4];\n}"
               :: "r"(dst), "l"(m), "r"(c1), "r"(c3), "r"(bar), "r"(expect) : "memory");
}
__device__ __forceinline__ void elect_tma3d(uint32_t dst, const CUtensorMap* m, int c1, int c2, uint32_t bar, uint32_t expect) {
  asm volatile("{\n.reg .pred p, q;\nelect.sync _|p, 0xffffffff;\nsetp.ne.and.u32 q, %5, 0, p;\n"
               "@q mbarrier.arrive.expect_tx.shared::cta.b64 _, [%4], %5;\n"
               "@p cp.async.bulk.tensor.3d.shared::cluster.global.mbarrier::complete_tx::bytes [%0], [%1, {0, %2, %3}], [%4];\n}"
               :: "r"(dst), "l"(m), "r"(c1), "r"(c2), "r"(bar), "r"(expect) : "memory");
}
__device__ __forceinline__ void elect_arrive(uint32_t a) {
  asm volatile("{\n.reg .pred p;\nelect.sync _|p, 0xffffffff;\n@p mbarrier.arrive.shared::cta.b64 _, [%0];\n}" :: "r"(a) : "memory");
}
__device__ __forceinline__ void elect_red_release(unsigned* a, unsigned v) {
  asm volatile("{\n.reg .pred p;\nelect.sync _|p, 0xffffffff;\n@p red.release.gpu.global.add.u32 [%0], %1;\n}" :: "l"(a), "r"(v) : "memory");
}
__device__ __forceinline__ void bulk_load(uint32_t dst, const void* src, uint32_t bytes, uint32_t bar) {
  asm volatile("cp.async.bulk.shared::cluster.global.mbarrier::complete_tx::bytes [%0], [%1], %2, [%3];"
               :: "r"(dst), "l"(src), "r"(bytes), "r"(bar) : "memory");
}
__device__ __forceinline__ void tma4d(uint32_t dst, const CUtensorMap* m, int c0, int c1, int c2, int c3, uint32_t bar) {
  asm volatile("cp.async.bulk.tensor.4d.shared::cluster.global.mbarrier::complete_tx::bytes [%0], [%1, {%2,%3,%4,%5}], [%6];"
               :: "r"(dst), "l"(m), "r"(c0), "r"(c1), "r"(c2), "r"(c3), "r"(bar) : "memory");
}
__device__ __forceinline__ void tma3d(uint32_t dst, const CUtensorMap* m, int c0, int c1, int c2, uint32_t bar) {
  asm volatile("cp.async.bulk.tensor.3d.shared::cluster.global.mbarrier::complete_tx::bytes [%0], [%1, {%2,%3,%4}], [%5];"
               :: "r"(dst), "l"(m), "r"(c0), "r"(c1), "r"(c2), "r"(bar) : "memory");
}
__device__ __forceinline__ void fence_async_smem() { asm volatile("fence.proxy.async.shared::cta;" ::: "memory"); }
__device__ __forceinline__ void fence_async_all() { asm volatile("fence.proxy.async;" ::: "memory"); }
__device__ __forceinline__ unsigned ld_relaxed(const unsigned* p) { unsigned v; asm volatile("ld.relaxed.gpu.global.u32 %0, [%1];" : "=r"(v) : "l"(p) : "memory"); return v; }
__device__ __forceinline__ void fence_acq() { asm volatile("fence.acq_rel.gpu;" ::: "memory"); }
__device__ __forceinline__ void red_release(unsigned* p, unsigned v) { asm volatile("red.release.gpu.global.add.u32 [%0], %1;" :: "l"(p), "r"(v) : "memory"); }
__device__ __forceinline__ void wait_flag(const unsigned* p, unsigned target) {
  int n = 0;
  while ((int)(ld_relaxed(p) - target) < 0) { if (++n > SPIN_LIMIT) __trap(); }
  fence_acq();
}
__device__ __forceinline__ void bar_sync(int id, int n) { asm volatile("bar.sync %0, %1;" :: "r"(id), "r"(n) : "memory"); }
__device__ __forceinline__ int bar_or(int id, int n, int v) {
  int r;
  asm volatile("{\n.reg .pred p, q;\nsetp.ne.s32 p, %1, 0;\nbar.red.or.pred q, %2, %3, p;\nselp.s32 %0, 1, 0, q;\n}" : "=r"(r) : "r"(v), "r"(id), "r"(n) : "memory");
  return r;
}
__device__ __forceinline__ uint32_t pack_bf16(float lo, float hi) { uint32_t r; asm("cvt.rn.bf16x2.f32 %0, %1, %2;" : "=r"(r) : "f"(hi), "f"(lo)); return r; }
__device__ __forceinline__ float bf16r(float x) { return __uint_as_float(pack_bf16(0.f, x) & 0xFFFF0000u); }
__device__ __forceinline__ float bf_lo(uint32_t v) { return __uint_as_float(v << 16); }
__device__ __forceinline__ float bf_hi(uint32_t v) { return __uint_as_float(v & 0xFFFF0000u); }
__device__ __forceinline__ float ex2(float x) { float y; asm("ex2.approx.ftz.f32 %0, %1;" : "=f"(y) : "f"(x)); return y; }
__device__ __forceinline__ void sts32(uint32_t a, uint32_t v) { asm volatile("st.shared.u32 [%0], %1;" :: "r"(a), "r"(v) : "memory"); }
__device__ __forceinline__ void sts128(uint32_t a, uint32_t x, uint32_t y, uint32_t z, uint32_t w) {
  asm volatile("st.shared.v4.u32 [%0], {%1,%2,%3,%4};" :: "r"(a), "r"(x), "r"(y), "r"(z), "r"(w) : "memory");
}

__device__ __forceinline__ uint32_t exp2_pair_mufu(float a, float b) { return pack_bf16(ex2(a), ex2(b)); }
__device__ __forceinline__ uint32_t exp2_pair_fma(float a, float b, float c, uint32_t kmant, uint32_t kexpo) {
  float z0, z1;
  uint32_t t, v, e, r;
  asm("fma.rn.f32 %0, %1, 0f00000080, %2;" : "=f"(z0) : "f"(a), "f"(c));
  asm("fma.rn.f32 %0, %1, 0f00000080, %2;" : "=f"(z1) : "f"(b), "f"(c));
  asm("cvt.pack.sat.s16.s32 %0, %1, %2;" : "=r"(t) : "r"(__float_as_uint(z1)), "r"(__float_as_uint(z0)));
  asm("lop3.b32 %0, %1, 0x007F007F, %2, 0xEA;" : "=r"(v) : "r"(t), "r"(kmant));
  asm("lop3.b32 %0, %1, 0x7F807F80, %2, 0xEA;" : "=r"(e) : "r"(t), "r"(kexpo));
  asm("fma.rn.bf16x2 %0, %1, %2, %3;" : "=r"(r) : "r"(t), "r"(v), "r"(e));
  return r;
}

__device__ __forceinline__ void wg_ss_n96_t(float* d, uint64_t da, uint64_t db, int sd) {
  asm volatile("{\n.reg .pred p;\nsetp.ne.b32 p, %50, 0;\n"
    "wgmma.mma_async.sync.aligned.m64n96k16.f32.bf16.bf16 {%0,%1,%2,%3,%4,%5,%6,%7,%8,%9,%10,%11,%12,%13,%14,%15,%16,%17,%18,%19,%20,%21,%22,%23,%24,%25,%26,%27,%28,%29,%30,%31,%32,%33,%34,%35,%36,%37,%38,%39,%40,%41,%42,%43,%44,%45,%46,%47}, %48, %49, p, 1, 1, 0, 1;\n}\n"
    : "+f"(d[0]),"+f"(d[1]),"+f"(d[2]),"+f"(d[3]),"+f"(d[4]),"+f"(d[5]),"+f"(d[6]),"+f"(d[7]),"+f"(d[8]),"+f"(d[9]),"+f"(d[10]),"+f"(d[11]),"+f"(d[12]),"+f"(d[13]),"+f"(d[14]),"+f"(d[15]),"+f"(d[16]),"+f"(d[17]),"+f"(d[18]),"+f"(d[19]),"+f"(d[20]),"+f"(d[21]),"+f"(d[22]),"+f"(d[23]),"+f"(d[24]),"+f"(d[25]),"+f"(d[26]),"+f"(d[27]),"+f"(d[28]),"+f"(d[29]),"+f"(d[30]),"+f"(d[31]),"+f"(d[32]),"+f"(d[33]),"+f"(d[34]),"+f"(d[35]),"+f"(d[36]),"+f"(d[37]),"+f"(d[38]),"+f"(d[39]),"+f"(d[40]),"+f"(d[41]),"+f"(d[42]),"+f"(d[43]),"+f"(d[44]),"+f"(d[45]),"+f"(d[46]),"+f"(d[47])
    : "l"(da), "l"(db), "r"(sd));
}
__device__ __forceinline__ void wg_ss_n32_t(float* d, uint64_t da, uint64_t db, int sd) {
  asm volatile("{\n.reg .pred p;\nsetp.ne.b32 p, %18, 0;\n"
    "wgmma.mma_async.sync.aligned.m64n32k16.f32.bf16.bf16 {%0,%1,%2,%3,%4,%5,%6,%7,%8,%9,%10,%11,%12,%13,%14,%15}, %16, %17, p, 1, 1, 0, 1;\n}\n"
    : "+f"(d[0]),"+f"(d[1]),"+f"(d[2]),"+f"(d[3]),"+f"(d[4]),"+f"(d[5]),"+f"(d[6]),"+f"(d[7]),"+f"(d[8]),"+f"(d[9]),"+f"(d[10]),"+f"(d[11]),"+f"(d[12]),"+f"(d[13]),"+f"(d[14]),"+f"(d[15])
    : "l"(da), "l"(db), "r"(sd));
}
__device__ __forceinline__ void wg_rs_n24(float* d, const uint32_t* a, uint64_t db, int sd) {
  asm volatile("{\n.reg .pred p;\nsetp.ne.b32 p, %17, 0;\n"
    "wgmma.mma_async.sync.aligned.m64n24k16.f32.bf16.bf16 {%0,%1,%2,%3,%4,%5,%6,%7,%8,%9,%10,%11}, {%12,%13,%14,%15}, %16, p, 1, 1, 0;\n}\n"
    : "+f"(d[0]),"+f"(d[1]),"+f"(d[2]),"+f"(d[3]),"+f"(d[4]),"+f"(d[5]),"+f"(d[6]),"+f"(d[7]),"+f"(d[8]),"+f"(d[9]),"+f"(d[10]),"+f"(d[11])
    : "r"(a[0]),"r"(a[1]),"r"(a[2]),"r"(a[3]), "l"(db), "r"(sd));
}
__device__ __forceinline__ void wg_rs_n40(float* d, const uint32_t* a, uint64_t db, int sd) {
  asm volatile("{\n.reg .pred p;\nsetp.ne.b32 p, %25, 0;\n"
    "wgmma.mma_async.sync.aligned.m64n40k16.f32.bf16.bf16 {%0,%1,%2,%3,%4,%5,%6,%7,%8,%9,%10,%11,%12,%13,%14,%15,%16,%17,%18,%19}, {%20,%21,%22,%23}, %24, p, 1, 1, 0;\n}\n"
    : "+f"(d[0]),"+f"(d[1]),"+f"(d[2]),"+f"(d[3]),"+f"(d[4]),"+f"(d[5]),"+f"(d[6]),"+f"(d[7]),"+f"(d[8]),"+f"(d[9]),"+f"(d[10]),"+f"(d[11]),"+f"(d[12]),"+f"(d[13]),"+f"(d[14]),"+f"(d[15]),"+f"(d[16]),"+f"(d[17]),"+f"(d[18]),"+f"(d[19])
    : "r"(a[0]),"r"(a[1]),"r"(a[2]),"r"(a[3]), "l"(db), "r"(sd));
}
__device__ __forceinline__ void wg_rs_n64(float* d, const uint32_t* a, uint64_t db, int sd) {
  asm volatile("{\n.reg .pred p;\nsetp.ne.b32 p, %37, 0;\n"
    "wgmma.mma_async.sync.aligned.m64n64k16.f32.bf16.bf16 {%0,%1,%2,%3,%4,%5,%6,%7,%8,%9,%10,%11,%12,%13,%14,%15,%16,%17,%18,%19,%20,%21,%22,%23,%24,%25,%26,%27,%28,%29,%30,%31}, {%32,%33,%34,%35}, %36, p, 1, 1, 0;\n}\n"
    : "+f"(d[0]),"+f"(d[1]),"+f"(d[2]),"+f"(d[3]),"+f"(d[4]),"+f"(d[5]),"+f"(d[6]),"+f"(d[7]),"+f"(d[8]),"+f"(d[9]),"+f"(d[10]),"+f"(d[11]),"+f"(d[12]),"+f"(d[13]),"+f"(d[14]),"+f"(d[15]),"+f"(d[16]),"+f"(d[17]),"+f"(d[18]),"+f"(d[19]),"+f"(d[20]),"+f"(d[21]),"+f"(d[22]),"+f"(d[23]),"+f"(d[24]),"+f"(d[25]),"+f"(d[26]),"+f"(d[27]),"+f"(d[28]),"+f"(d[29]),"+f"(d[30]),"+f"(d[31])
    : "r"(a[0]),"r"(a[1]),"r"(a[2]),"r"(a[3]), "l"(db), "r"(sd));
}
__device__ __forceinline__ void wg_rs_n24_t(float* d, const uint32_t* a, uint64_t db, int sd) {
  asm volatile("{\n.reg .pred p;\nsetp.ne.b32 p, %17, 0;\n"
    "wgmma.mma_async.sync.aligned.m64n24k16.f32.bf16.bf16 {%0,%1,%2,%3,%4,%5,%6,%7,%8,%9,%10,%11}, {%12,%13,%14,%15}, %16, p, 1, 1, 1;\n}\n"
    : "+f"(d[0]),"+f"(d[1]),"+f"(d[2]),"+f"(d[3]),"+f"(d[4]),"+f"(d[5]),"+f"(d[6]),"+f"(d[7]),"+f"(d[8]),"+f"(d[9]),"+f"(d[10]),"+f"(d[11])
    : "r"(a[0]),"r"(a[1]),"r"(a[2]),"r"(a[3]), "l"(db), "r"(sd));
}
#define KPERM 0x72651430u
#define NMUFU 24
#define QK_S0 do { \
  wg_fence(); \
  wg_rs_n24(s0, qa, daug, 0); wg_rs_n24(s0, qf, dkt, 1); DESC_ADD(dkt, 48); \
  wg_rs_n40(s0 + 12, qf, dkt, 0); DESC_ADD(dkt, 80); \
  wg_commit(); \
} while (0)
#define EXP_PV_S0 do { \
  pr[0] = exp2_pair_mufu(s0[0], s0[1]); \
  pr[1] = exp2_pair_mufu(s0[2], s0[3]); \
  pr[2] = exp2_pair_fma(s0[12], s0[13], c0, kmant, kexpo); \
  pr[3] = exp2_pair_fma(s0[14], s0[15], c1, kmant, kexpo); \
  pr[4] = exp2_pair_fma(s0[16], s0[17], c0, kmant, kexpo); \
  pr[5] = exp2_pair_fma(s0[18], s0[19], c1, kmant, kexpo); \
  pr[6] = exp2_pair_mufu(s0[4], s0[5]); \
  pr[7] = exp2_pair_mufu(s0[6], s0[7]); \
  PIN_R(pr[0]); \
  PIN_R(pr[1]); \
  PIN_R(pr[2]); \
  PIN_R(pr[3]); \
  PIN_R(pr[4]); \
  PIN_R(pr[5]); \
  PIN_R(pr[6]); \
  PIN_R(pr[7]); \
  wg_fence(); \
  wg_rs_n24_t(o, pr + 0, dvt, 1); DESC_ADD(dvt, 16); \
  wg_rs_n24_t(o, pr + 4, dvt, 1); DESC_ADD(dvt, 16); \
  pr[8] = exp2_pair_fma(s0[20], s0[21], c0, kmant, kexpo); \
  pr[9] = exp2_pair_fma(s0[22], s0[23], c1, kmant, kexpo); \
  pr[10] = exp2_pair_fma(s0[24], s0[25], c0, kmant, kexpo); \
  pr[11] = exp2_pair_fma(s0[26], s0[27], c1, kmant, kexpo); \
  pr[12] = exp2_pair_mufu(s0[8], s0[9]); \
  pr[13] = exp2_pair_mufu(s0[10], s0[11]); \
  pr[14] = exp2_pair_fma(s0[28], s0[29], c0, kmant, kexpo); \
  pr[15] = exp2_pair_fma(s0[30], s0[31], c1, kmant, kexpo); \
  PIN_R(pr[8]); \
  PIN_R(pr[9]); \
  PIN_R(pr[10]); \
  PIN_R(pr[11]); \
  PIN_R(pr[12]); \
  PIN_R(pr[13]); \
  PIN_R(pr[14]); \
  PIN_R(pr[15]); \
  wg_fence(); \
  wg_rs_n24_t(o, pr + 8, dvt, 1); DESC_ADD(dvt, 16); \
  wg_rs_n24_t(o, pr + 12, dvt, 1); DESC_ADD(dvt, 16); \
  wg_commit(); \
} while (0)
#define PIN_S0 do { \
  PIN_F(s0[0]); \
  PIN_F(s0[1]); \
  PIN_F(s0[2]); \
  PIN_F(s0[3]); \
  PIN_F(s0[4]); \
  PIN_F(s0[5]); \
  PIN_F(s0[6]); \
  PIN_F(s0[7]); \
  PIN_F(s0[8]); \
  PIN_F(s0[9]); \
  PIN_F(s0[10]); \
  PIN_F(s0[11]); \
  PIN_F(s0[12]); \
  PIN_F(s0[13]); \
  PIN_F(s0[14]); \
  PIN_F(s0[15]); \
  PIN_F(s0[16]); \
  PIN_F(s0[17]); \
  PIN_F(s0[18]); \
  PIN_F(s0[19]); \
  PIN_F(s0[20]); \
  PIN_F(s0[21]); \
  PIN_F(s0[22]); \
  PIN_F(s0[23]); \
  PIN_F(s0[24]); \
  PIN_F(s0[25]); \
  PIN_F(s0[26]); \
  PIN_F(s0[27]); \
  PIN_F(s0[28]); \
  PIN_F(s0[29]); \
  PIN_F(s0[30]); \
  PIN_F(s0[31]); \
} while (0)
#define QK_S1 do { \
  wg_fence(); \
  wg_rs_n24(s1, qa, daug, 0); wg_rs_n24(s1, qf, dkt, 1); DESC_ADD(dkt, 48); \
  wg_rs_n40(s1 + 12, qf, dkt, 0); DESC_ADD(dkt, 80); \
  wg_commit(); \
} while (0)
#define EXP_PV_S1 do { \
  pr[0] = exp2_pair_mufu(s1[0], s1[1]); \
  pr[1] = exp2_pair_mufu(s1[2], s1[3]); \
  pr[2] = exp2_pair_fma(s1[12], s1[13], c0, kmant, kexpo); \
  pr[3] = exp2_pair_fma(s1[14], s1[15], c1, kmant, kexpo); \
  pr[4] = exp2_pair_fma(s1[16], s1[17], c0, kmant, kexpo); \
  pr[5] = exp2_pair_fma(s1[18], s1[19], c1, kmant, kexpo); \
  pr[6] = exp2_pair_mufu(s1[4], s1[5]); \
  pr[7] = exp2_pair_mufu(s1[6], s1[7]); \
  PIN_R(pr[0]); \
  PIN_R(pr[1]); \
  PIN_R(pr[2]); \
  PIN_R(pr[3]); \
  PIN_R(pr[4]); \
  PIN_R(pr[5]); \
  PIN_R(pr[6]); \
  PIN_R(pr[7]); \
  wg_fence(); \
  wg_rs_n24_t(o, pr + 0, dvt, 1); DESC_ADD(dvt, 16); \
  wg_rs_n24_t(o, pr + 4, dvt, 1); DESC_ADD(dvt, 16); \
  pr[8] = exp2_pair_fma(s1[20], s1[21], c0, kmant, kexpo); \
  pr[9] = exp2_pair_fma(s1[22], s1[23], c1, kmant, kexpo); \
  pr[10] = exp2_pair_fma(s1[24], s1[25], c0, kmant, kexpo); \
  pr[11] = exp2_pair_fma(s1[26], s1[27], c1, kmant, kexpo); \
  pr[12] = exp2_pair_mufu(s1[8], s1[9]); \
  pr[13] = exp2_pair_mufu(s1[10], s1[11]); \
  pr[14] = exp2_pair_fma(s1[28], s1[29], c0, kmant, kexpo); \
  pr[15] = exp2_pair_fma(s1[30], s1[31], c1, kmant, kexpo); \
  PIN_R(pr[8]); \
  PIN_R(pr[9]); \
  PIN_R(pr[10]); \
  PIN_R(pr[11]); \
  PIN_R(pr[12]); \
  PIN_R(pr[13]); \
  PIN_R(pr[14]); \
  PIN_R(pr[15]); \
  wg_fence(); \
  wg_rs_n24_t(o, pr + 8, dvt, 1); DESC_ADD(dvt, 16); \
  wg_rs_n24_t(o, pr + 12, dvt, 1); DESC_ADD(dvt, 16); \
  wg_commit(); \
} while (0)
#define PIN_S1 do { \
  PIN_F(s1[0]); \
  PIN_F(s1[1]); \
  PIN_F(s1[2]); \
  PIN_F(s1[3]); \
  PIN_F(s1[4]); \
  PIN_F(s1[5]); \
  PIN_F(s1[6]); \
  PIN_F(s1[7]); \
  PIN_F(s1[8]); \
  PIN_F(s1[9]); \
  PIN_F(s1[10]); \
  PIN_F(s1[11]); \
  PIN_F(s1[12]); \
  PIN_F(s1[13]); \
  PIN_F(s1[14]); \
  PIN_F(s1[15]); \
  PIN_F(s1[16]); \
  PIN_F(s1[17]); \
  PIN_F(s1[18]); \
  PIN_F(s1[19]); \
  PIN_F(s1[20]); \
  PIN_F(s1[21]); \
  PIN_F(s1[22]); \
  PIN_F(s1[23]); \
  PIN_F(s1[24]); \
  PIN_F(s1[25]); \
  PIN_F(s1[26]); \
  PIN_F(s1[27]); \
  PIN_F(s1[28]); \
  PIN_F(s1[29]); \
  PIN_F(s1[30]); \
  PIN_F(s1[31]); \
} while (0)
#define PIN_O do { \
  PIN_F(o[0]); \
  PIN_F(o[1]); \
  PIN_F(o[2]); \
  PIN_F(o[3]); \
  PIN_F(o[4]); \
  PIN_F(o[5]); \
  PIN_F(o[6]); \
  PIN_F(o[7]); \
  PIN_F(o[8]); \
  PIN_F(o[9]); \
  PIN_F(o[10]); \
  PIN_F(o[11]); \
} while (0)
#define PIN_ACC48 do { \
  PIN_F(acc[0]); \
  PIN_F(acc[1]); \
  PIN_F(acc[2]); \
  PIN_F(acc[3]); \
  PIN_F(acc[4]); \
  PIN_F(acc[5]); \
  PIN_F(acc[6]); \
  PIN_F(acc[7]); \
  PIN_F(acc[8]); \
  PIN_F(acc[9]); \
  PIN_F(acc[10]); \
  PIN_F(acc[11]); \
  PIN_F(acc[12]); \
  PIN_F(acc[13]); \
  PIN_F(acc[14]); \
  PIN_F(acc[15]); \
  PIN_F(acc[16]); \
  PIN_F(acc[17]); \
  PIN_F(acc[18]); \
  PIN_F(acc[19]); \
  PIN_F(acc[20]); \
  PIN_F(acc[21]); \
  PIN_F(acc[22]); \
  PIN_F(acc[23]); \
  PIN_F(acc[24]); \
  PIN_F(acc[25]); \
  PIN_F(acc[26]); \
  PIN_F(acc[27]); \
  PIN_F(acc[28]); \
  PIN_F(acc[29]); \
  PIN_F(acc[30]); \
  PIN_F(acc[31]); \
  PIN_F(acc[32]); \
  PIN_F(acc[33]); \
  PIN_F(acc[34]); \
  PIN_F(acc[35]); \
  PIN_F(acc[36]); \
  PIN_F(acc[37]); \
  PIN_F(acc[38]); \
  PIN_F(acc[39]); \
  PIN_F(acc[40]); \
  PIN_F(acc[41]); \
  PIN_F(acc[42]); \
  PIN_F(acc[43]); \
  PIN_F(acc[44]); \
  PIN_F(acc[45]); \
  PIN_F(acc[46]); \
  PIN_F(acc[47]); \
} while (0)
#define PIN_ACC16 do { \
  PIN_F(acc2[0]); \
  PIN_F(acc2[1]); \
  PIN_F(acc2[2]); \
  PIN_F(acc2[3]); \
  PIN_F(acc2[4]); \
  PIN_F(acc2[5]); \
  PIN_F(acc2[6]); \
  PIN_F(acc2[7]); \
  PIN_F(acc2[8]); \
  PIN_F(acc2[9]); \
  PIN_F(acc2[10]); \
  PIN_F(acc2[11]); \
  PIN_F(acc2[12]); \
  PIN_F(acc2[13]); \
  PIN_F(acc2[14]); \
  PIN_F(acc2[15]); \
} while (0)

__device__ __noinline__ void attn_fallback(uint32_t q0, uint32_t q1, uint32_t q2, uint32_t q3, const uint8_t* kvh,
                                           uint8_t* odst, uint32_t* qscr, int barid) {
  const int t128 = threadIdx.x & 127, lane = t128 & 31, wq = t128 >> 5, g = lane >> 2, t = lane & 3;
  qscr[(16 * wq + g) * 8 + t] = q0;
  qscr[(16 * wq + g + 8) * 8 + t] = q1;
  qscr[(16 * wq + g) * 8 + 4 + t] = q2;
  qscr[(16 * wq + g + 8) * 8 + 4 + t] = q3;
  __threadfence();
  bar_sync(barid, 128);
  const int row = t128 >> 1, par = t128 & 1;
  float q[16], o[16];
#pragma unroll
  for (int i = 0; i < 8; i++) { uint32_t v = __ldcg(qscr + row * 8 + i); q[2 * i] = bf_lo(v); q[2 * i + 1] = bf_hi(v); }
#pragma unroll
  for (int i = 0; i < 16; i++) o[i] = 0.f;
  float m = -INFINITY, l = 0.f;
#pragma unroll 1
  for (int key = par * 1024; key < par * 1024 + 1024; key++) {
    const int blk = key >> 7, kk = key & 127, G = kk >> 3;
    const uint8_t* kp = kvh + blk * 8192 + (G >> 3) * 2048 + ((KPERM >> (4 * (G & 7))) & 7) * 256 + (kk & 7) * 16;
    const uint8_t* vp = kvh + blk * 8192 + 4096 + kk * 16;
    const uint4 k0 = __ldcg((const uint4*)kp), k1 = __ldcg((const uint4*)(kp + 128));
    const uint4 v0 = __ldcg((const uint4*)vp), v1 = __ldcg((const uint4*)(vp + 2048));
    const uint32_t kw[8] = {k0.x, k0.y, k0.z, k0.w, k1.x, k1.y, k1.z, k1.w};
    const uint32_t vw[8] = {v0.x, v0.y, v0.z, v0.w, v1.x, v1.y, v1.z, v1.w};
    float s = 0.f;
#pragma unroll
    for (int i = 0; i < 8; i++) { s = fmaf(q[2 * i], bf_lo(kw[i]), s); s = fmaf(q[2 * i + 1], bf_hi(kw[i]), s); }
    if (s == -INFINITY) continue;
    const float mn = fmaxf(m, s), a = exp2f(m - mn), p = exp2f(s - mn);
    m = mn;
    l = l * a + p;
#pragma unroll
    for (int i = 0; i < 8; i++) { o[2 * i] = o[2 * i] * a + p * bf_lo(vw[i]); o[2 * i + 1] = o[2 * i + 1] * a + p * bf_hi(vw[i]); }
  }
  const float m2 = __shfl_xor_sync(0xffffffffu, m, 1), l2 = __shfl_xor_sync(0xffffffffu, l, 1);
  const float mn = fmaxf(m, m2);
  const float a = (m == -INFINITY) ? 0.f : exp2f(m - mn), a2 = (m2 == -INFINITY) ? 0.f : exp2f(m2 - mn);
  const float inv = 1.0f / (l * a + l2 * a2);
  uint32_t w[4];
#pragma unroll
  for (int i = 0; i < 16; i++) { const float other = __shfl_xor_sync(0xffffffffu, o[i], 1); o[i] = (o[i] * a + other * a2) * inv; }
#pragma unroll
  for (int i = 0; i < 4; i++) w[i] = par ? pack_bf16(o[8 + 2 * i], o[9 + 2 * i]) : pack_bf16(o[2 * i], o[2 * i + 1]);
  *(uint4*)(odst + (row >> 3) * 256 + par * 128 + (row & 7) * 16) = make_uint4(w[0], w[1], w[2], w[3]);
  bar_sync(barid, 128);
}

__device__ __forceinline__ void ffn_cta(int j, uint8_t* sm, const __nv_bfloat16* wgate, const __nv_bfloat16* wup,
                                        const __nv_bfloat16* wdown) {
  const int tid = threadIdx.x;
  float* xs = (float*)sm;
  float* hs = xs + 512;
  float* red = xs + 1024;
  unsigned* ep = (unsigned*)(red + 4096);
  if (tid == 0) *ep = atomicAdd(&g_start, 1u) / NCTA + 1u;
  __syncthreads();
  const unsigned e1 = *ep;
  if (tid < 16) wait_flag(&g_ln[tid * 32], e1 * 8u);
  __syncthreads();
  if (tid >= 64 && tid < 92)
    asm volatile("cp.async.bulk.prefetch.L2.global [%0], 16384;" :: "l"((const uint8_t*)(wdown + (size_t)448 * j * 512) + (tid - 64) * 16384) : "memory");
  if (tid < 64) {
    const unsigned key = (unsigned)__ldcg(&g_best);
    const int idx = 2047 - (int)(key & 0xFFFFu), rr = idx & 127;
    const uint4 v = __ldcg((const uint4*)(g_xn + (idx >> 7) * 131072 + (tid >> 3) * 16384 + rr * 128 + (((tid & 7) ^ (rr & 7)) << 4)));
    float* d = xs + tid * 8;
    d[0] = bf_lo(v.x); d[1] = bf_hi(v.x); d[2] = bf_lo(v.y); d[3] = bf_hi(v.y);
    d[4] = bf_lo(v.z); d[5] = bf_hi(v.z); d[6] = bf_lo(v.w); d[7] = bf_hi(v.w);
  }
  __syncthreads();
  if (tid < 448) {
    const int kg = tid / 112, r = tid % 112, mat = r / 56, cg = r % 56;
    const uint4* p = (const uint4*)((mat ? wup : wgate) + (size_t)kg * 128 * 1792 + 448 * j + cg * 8);
    float a[8] = {0.f, 0.f, 0.f, 0.f, 0.f, 0.f, 0.f, 0.f};
#pragma unroll 1
    for (int k0 = 0; k0 < 128; k0 += 16) {
      uint4 w[16];
#pragma unroll
      for (int k = 0; k < 16; k++) w[k] = __ldg(p + (size_t)(k0 + k) * 224);
#pragma unroll
      for (int k = 0; k < 16; k++) {
        const float x = xs[kg * 128 + k0 + k];
        a[0] = fmaf(x, bf_lo(w[k].x), a[0]); a[1] = fmaf(x, bf_hi(w[k].x), a[1]);
        a[2] = fmaf(x, bf_lo(w[k].y), a[2]); a[3] = fmaf(x, bf_hi(w[k].y), a[3]);
        a[4] = fmaf(x, bf_lo(w[k].z), a[4]); a[5] = fmaf(x, bf_hi(w[k].z), a[5]);
        a[6] = fmaf(x, bf_lo(w[k].w), a[6]); a[7] = fmaf(x, bf_hi(w[k].w), a[7]);
      }
    }
    float* d = red + (kg * 2 + mat) * 448 + cg * 8;
#pragma unroll
    for (int i = 0; i < 8; i++) d[i] = a[i];
  }
  __syncthreads();
  if (tid < 448) {
    const float gv = bf16r(red[tid] + red[896 + tid] + red[1792 + tid] + red[2688 + tid]);
    const float uv = bf16r(red[448 + tid] + red[1344 + tid] + red[2240 + tid] + red[3136 + tid]);
    const float sg = bf16r(gv / (1.0f + expf(-gv)));
    hs[tid] = bf16r(sg * uv);
  }
  __syncthreads();
  {
    const int cg = tid & 63, kg = tid >> 6;
    const uint4* p = (const uint4*)(wdown + (size_t)(448 * j + kg * 56) * 512 + cg * 8);
    float a[8] = {0.f, 0.f, 0.f, 0.f, 0.f, 0.f, 0.f, 0.f};
#pragma unroll 1
    for (int k0 = 0; k0 < 56; k0 += 14) {
      uint4 w[14];
#pragma unroll
      for (int k = 0; k < 14; k++) w[k] = __ldg(p + (size_t)(k0 + k) * 64);
#pragma unroll
      for (int k = 0; k < 14; k++) {
        const float x = hs[kg * 56 + k0 + k];
        a[0] = fmaf(x, bf_lo(w[k].x), a[0]); a[1] = fmaf(x, bf_hi(w[k].x), a[1]);
        a[2] = fmaf(x, bf_lo(w[k].y), a[2]); a[3] = fmaf(x, bf_hi(w[k].y), a[3]);
        a[4] = fmaf(x, bf_lo(w[k].z), a[4]); a[5] = fmaf(x, bf_hi(w[k].z), a[5]);
        a[6] = fmaf(x, bf_lo(w[k].w), a[6]); a[7] = fmaf(x, bf_hi(w[k].w), a[7]);
      }
    }
    float* d = red + kg * 512 + cg * 8;
#pragma unroll
    for (int i = 0; i < 8; i++) d[i] = a[i];
  }
  __syncthreads();
  float y = 0.f;
#pragma unroll
  for (int k = 0; k < 8; k++) y += red[k * 512 + tid];
  g_y[j * 512 + tid] = y;
  __syncthreads();
  if (tid == 0) red_release(&g_ffn, 1u);
}

__global__ void __cluster_dims__(2, 1, 1) __launch_bounds__(512, 1)
fused_kernel(const __grid_constant__ CUtensorMap tm_wqkv, const __grid_constant__ CUtensorMap tm_wo,
             const __nv_bfloat16* __restrict__ x, const __nv_bfloat16* __restrict__ wr,
             const __nv_bfloat16* __restrict__ wgate, const __nv_bfloat16* __restrict__ wup,
             const __nv_bfloat16* __restrict__ wdown, __nv_bfloat16* __restrict__ out) {
  extern __shared__ __align__(1024) uint8_t smem[];
  const int b = blockIdx.x;
  if (b >= 128) { ffn_cta(b - 128, smem, wgate, wup, wdown); return; }
  const int tid = threadIdx.x, lane = tid & 31;
  const int warp = (int)__reduce_max_sync(0xffffffffu, (unsigned)tid >> 5);
  const int wgi = warp >> 2, wq = warp & 3, hf = wgi & 1, s = wgi >> 1;
  const int g = lane >> 2, t = lane & 3;
  const int rb = b & 15, cb = b >> 4;
  const uint32_t sb = (uint32_t)__cvta_generic_to_shared(smem);
  const uint32_t bar = sb + SM_BAR;
  volatile unsigned* misc = (volatile unsigned*)(smem + SM_MISC);

  const int rr = cb * 16 + warp;
  const uint4 xa = __ldg((const uint4*)(x + (size_t)(rb * 128 + rr) * 512 + lane * 8));
  const uint4 xb = __ldg((const uint4*)(x + (size_t)(rb * 128 + rr) * 512 + 256 + lane * 8));
  const uint4 wa = __ldg((const uint4*)(wr + lane * 8));
  const uint4 wb = __ldg((const uint4*)(wr + 256 + lane * 8));
  if (tid == 0) {
    for (int i = 0; i < 5; i++) mbar_init(bar + B_FULLA + 8 * i, 1);
    for (int i = 0; i < 3; i++) mbar_init(bar + B_EMPTYA + 8 * i, 4);
    for (int i = 0; i < 8; i++) { mbar_init(bar + B_FULLR + 8 * i, 1); mbar_init(bar + B_EMPTYR + 8 * i, 2); }
    mbar_init(bar + B_WO, 1); mbar_init(bar + B_OG0, 1); mbar_init(bar + B_OG1, 1);
    asm volatile("fence.mbarrier_init.release.cluster;" ::: "memory");
    fence_async_smem();
    for (int j = 0; j < 5; j++) {
      mbar_expect(bar + B_FULLA + 8 * j, A_STAGE);
      tma4d(sb + j * A_STAGE + A_WOFF, &tm_wqkv, 0, 64 * j, 0, 2 * cb, bar + B_FULLA + 8 * j);
    }
    mbar_arrive(bar + B_FULLR);
    mbar_arrive(bar + B_FULLR + 32);
  }
  if (tid == 32) misc[16] = atomicAdd(&g_start, 1u) / NCTA + 1u;
  if (tid >= 64 && tid < 64 + 48) {
    const int i = tid - 64;
    const uint32_t one = ((i >> 3) & 1) ? 0u : 0x3F803F80u;
    sts128(sb + SM_AUG + i * 16, one, one, 0u, 0u);
  }
  {
    const uint32_t xw[8] = {xa.x, xa.y, xa.z, xa.w, xb.x, xb.y, xb.z, xb.w};
    const uint32_t ww[8] = {wa.x, wa.y, wa.z, wa.w, wb.x, wb.y, wb.z, wb.w};
    float f[16];
    float sum = 0.f;
#pragma unroll
    for (int i = 0; i < 8; i++) { f[2 * i] = bf_lo(xw[i]); f[2 * i + 1] = bf_hi(xw[i]); sum += f[2 * i] + f[2 * i + 1]; }
#pragma unroll
    for (int o = 16; o; o >>= 1) sum += __shfl_xor_sync(0xffffffffu, sum, o);
    const float mean = sum * (1.0f / 512.0f);
    float var = 0.f;
#pragma unroll
    for (int i = 0; i < 16; i++) { const float d = f[i] - mean; var = fmaf(d, d, var); }
#pragma unroll
    for (int o = 16; o; o >>= 1) var += __shfl_xor_sync(0xffffffffu, var, o);
    const float mb = bf16r(mean);
    const float sd = bf16r(sqrtf(bf16r(bf16r(var * (1.0f / 512.0f)) + 1e-5f)));
    const float rs = 1.0f / sd;
    uint32_t n[8];
    float r = 0.f;
#pragma unroll
    for (int i = 0; i < 8; i++) {
      const uint32_t d = pack_bf16(f[2 * i] - mb, f[2 * i + 1] - mb);
      n[i] = pack_bf16(bf_lo(d) * rs, bf_hi(d) * rs);
      r = fmaf(bf_lo(n[i]), bf_lo(ww[i]), r);
      r = fmaf(bf_hi(n[i]), bf_hi(ww[i]), r);
    }
    uint8_t* dst = g_xn + rb * 131072 + (lane >> 3) * 16384 + rr * 128 + (((lane & 7) ^ (rr & 7)) << 4);
    *(uint4*)dst = make_uint4(n[0], n[1], n[2], n[3]);
    *(uint4*)(dst + 65536) = make_uint4(n[4], n[5], n[6], n[7]);
#pragma unroll
    for (int o = 16; o; o >>= 1) r += __shfl_xor_sync(0xffffffffu, r, o);
    uint32_t rbits = pack_bf16(r + 0.0f, 0.f) & 0xFFFFu;
    rbits = (rbits & 0x8000u) ? (~rbits & 0xFFFFu) : (rbits | 0x8000u);
    if (r != r) rbits = 0u;
    if (lane == 0) misc[warp] = (rbits << 16) | (uint32_t)(2047 - (rb * 128 + rr));
  }
  fence_async_smem();
  __syncthreads();
  const unsigned e1 = __reduce_max_sync(0xffffffffu, misc[16]);
  if (warp == 0) {
    const unsigned key = __reduce_max_sync(0xffffffffu, misc[lane & 15]);
    asm volatile("{\n.reg .pred p;\nelect.sync _|p, 0xffffffff;\n@p red.relaxed.gpu.global.max.u64 [%0], %1;\n"
                 "@p red.release.gpu.global.add.u32 [%2], 1;\n}"
                 :: "l"(&g_best), "l"(((unsigned long long)e1 << 32) | key), "l"(&g_ln[rb * 32]) : "memory");
    wait_flag_warp(&g_ln[rb * 32], e1 * 8u);
#pragma unroll
    for (int j = 0; j < 5; j++) elect_load(sb + j * A_STAGE, g_xn + rb * 131072 + j * 16384, 16384, bar + B_FULLA + 8 * j, 0);
  }

  uint32_t qn[4];
  uint32_t qf[4];
  {
    float acc[48];
#pragma unroll
    for (int i = 0; i < 48; i++) acc[i] = 0.f;
#pragma unroll
    for (int j = 0; j < 8; j++) {
      const int sl = j % 5;
      mbar_wait(bar + B_FULLA + 8 * sl, j / 5);
      uint64_t da = mkdesc(sb + sl * A_STAGE + hf * 8192, 16, 1024, 1);
      uint64_t db = mkdesc(sb + sl * A_STAGE + A_WOFF + s * 12288, 4096, 512, 2);
      wg_fence();
#pragma unroll
      for (int kk = 0; kk < 4; kk++) { wg_ss_n96_t(acc, da, db, 1); DESC_ADD(da, 2); DESC_ADD(db, 64); }
      wg_commit();
      if (j >= 1 && j <= 3) {
        wg_wait<1>();
        if (wq == 0) elect_arrive(bar + B_EMPTYA + 8 * (j - 1));
        if (warp == 0) {
          mbar_wait(bar + B_EMPTYA + 8 * (j - 1), 0);
          const uint32_t fb = bar + B_FULLA + 8 * (j - 1);
          elect_tma4d(sb + (j - 1) * A_STAGE + A_WOFF, &tm_wqkv, 64 * (j + 4), 2 * cb, fb, A_STAGE);
          elect_load(sb + (j - 1) * A_STAGE, g_xn + rb * 131072 + (j + 4) * 16384, 16384, fb, 0);
        }
      }
    }
    wg_wait<0>();
    PIN_ACC48;
    bar_sync(1, 512);
    if (warp == 15) {
#pragma unroll
      for (int i = 0; i < 4; i++) elect_tma3d(sb + SM_WO + i * 16384, &tm_wo, 256 * (i & 1), 2 * cb + (i >> 1), bar + B_WO, i ? 0 : 65536);
    }
#pragma unroll
    for (int i = 0; i < 2; i++) {
      const int c = tid + 512 * i;
      sts128(sb + (c >> 9) * R_STREAM + ((c >> 7) & 3) * R_SLOT + 8192 + (c & 127) * 16, 0x00003F80u, 0u, 0u, 0u);
    }
    const float qs = 0.25f * 1.4426950408889634f;
#pragma unroll
    for (int i = 0; i < 4; i++) {
      const int o0 = (i >> 1) * 4 + (i & 1) * 2;
      qf[i] = pack_bf16(acc[o0] * qs, acc[o0 + 1] * qs);
      qn[i] = pack_bf16(acc[8 + o0] * qs, acc[8 + o0 + 1] * qs);
    }
#pragma unroll
    for (int u = 0; u < 2; u++) {
      const int i8 = 2 * wq + u;
      const uint32_t ko = hf * 2048 + ((KPERM >> (4 * i8)) & 7) * 256 + lane * 4;
      const uint32_t vo = 4096 + (hf * 8 + i8) * 128 + lane * 4;
#pragma unroll
      for (int hh = 0; hh < 2; hh++) {
        uint8_t* gp = g_kv + ((cb * 4 + s * 2 + hh) * 16 + rb) * 8192;
#pragma unroll
        for (int dh = 0; dh < 2; dh++) {
          const int jk = 4 + hh * 2 + dh, jv = 8 + hh * 2 + dh;
          const uint32_t kw = pack_bf16(acc[4 * jk + 2 * u], acc[4 * jk + 2 * u + 1]);
          const uint32_t vw = pack_bf16(acc[4 * jv + 2 * u], acc[4 * jv + 2 * u + 1]);
          *(uint32_t*)(gp + ko + dh * 128) = kw;
          *(uint32_t*)(gp + vo + dh * 2048) = vw;
          if (hh == 0) {
            sts32(sb + s * R_STREAM + ko + dh * 128, kw);
            sts32(sb + s * R_STREAM + vo + dh * 2048, vw);
          }
        }
      }
    }
    fence_async_smem();
    bar_sync(1, 512);
    if (warp == 4) elect_red_release(&g_kvf[cb * 32 + rb], 1u);
  }

  const uint32_t ring = sb + s * R_STREAM;
  const uint32_t bfull = bar + B_FULLR + 32 * s, bempty = bar + B_EMPTYR + 32 * s;
  const uint64_t daug = mkdesc(sb + SM_AUG, 128, 256, 0);
  const uint64_t dk0 = mkdesc(ring, 128, 256, 0);
  const uint64_t dv0 = mkdesc(ring + 4096, 128, 2048, 0);
  const bool loader = (hf == 0) && (wq == 0);
  uint32_t kmant = 0x3F003F00u, kexpo = 0x00010001u;
  PIN_R(kmant); PIN_R(kexpo);
  if (loader) {
    wait_flag_warp(&g_kvf[cb * 32 + (lane & 15)], e1);
#pragma unroll
    for (int n = 1; n < 4; n++) {
      const int blk = (n == 1) ? (rb ^ 1) : (((rb & ~1) + n) & 15);
      elect_load(ring + n * R_SLOT, g_kv + ((cb * 4 + s * 2) * 16 + blk) * 8192, 8192, bfull + 8 * n, 8192);
    }
  }
#pragma unroll 1
  for (int rnd = 0; rnd < 2; rnd++) {
    float s0[32], s1[32], o[12];
    uint32_t pr[16], qa[4];
    float c0, c1;
    int bad;
#pragma unroll
    for (int i = 0; i < 12; i++) o[i] = 0.f;
#pragma unroll
    for (int i = 0; i < 32; i++) { s0[i] = 0.f; s1[i] = 0.f; }
    uint64_t dkt = dk0, dvt = dv0;
    mbar_wait(bfull, 0);
    PIN_S0; PIN_S1; PIN_O;
    wg_fence();
    wg_rs_n24(s0, qf, dkt, 0);
    wg_rs_n40(s0 + 12, qf, dkt + 48, 0);
    DESC_ADD(dkt, 128);
    wg_commit();
    wg_wait<0>();
    PIN_S0;
    {
      float m0 = fmaxf(s0[0], s0[1]), m1 = fmaxf(s0[2], s0[3]);
#pragma unroll
      for (int j = 1; j < 8; j++) {
        m0 = fmaxf(m0, fmaxf(s0[4 * j], s0[4 * j + 1]));
        m1 = fmaxf(m1, fmaxf(s0[4 * j + 2], s0[4 * j + 3]));
      }
      m0 = fmaxf(m0, __shfl_xor_sync(0xffffffffu, m0, 1)); m1 = fmaxf(m1, __shfl_xor_sync(0xffffffffu, m1, 1));
      m0 = fmaxf(m0, __shfl_xor_sync(0xffffffffu, m0, 2)); m1 = fmaxf(m1, __shfl_xor_sync(0xffffffffu, m1, 2));
      m0 = -(ceilf(m0) + M_MARGIN);
      m1 = -(ceilf(m1) + M_MARGIN);
      bad = !(fabsf(m0) < 30000.f) || !(fabsf(m1) < 30000.f);
      const float p142 = __uint_as_float(0x00000080u);
      asm("mul.rn.f32 %0, %1, %2;" : "=f"(c0) : "f"(m0 + 127.f), "f"(p142));
      asm("mul.rn.f32 %0, %1, %2;" : "=f"(c1) : "f"(m1 + 127.f), "f"(p142));
      const float h0 = bf16r(m0), h1 = bf16r(m1);
      const uint32_t dl = 0xBAF03F18u;
      qa[0] = (t == 0) ? pack_bf16(h0, m0 - h0) : (t == 1 ? dl : 0u);
      qa[1] = (t == 0) ? pack_bf16(h1, m1 - h1) : (t == 1 ? dl : 0u);
      qa[2] = 0u; qa[3] = 0u;
      PIN_R(qa[0]); PIN_R(qa[1]); PIN_R(qa[2]); PIN_R(qa[3]);
    }
    wg_fence();
    wg_rs_n24(s0, qa, daug, 1);
    wg_commit();
    wg_wait<0>();
    PIN_S0;
#pragma unroll 1
    for (int i = 0; i < 16; i++) {
      const int n = rnd * 16 + i;
      QK_S1;
      EXP_PV_S0;
      wg_wait<0>();
      PIN_S1; PIN_O;
      const int nx = (i + 1) & 3;
      dkt = dk0 + (uint64_t)(nx * (R_SLOT / 16));
      if (i < 15) mbar_wait(bfull + 8 * nx, ((n + 1) >> 2) & 1);
      QK_S0;
      EXP_PV_S1;
      wg_wait<0>();
      PIN_S0; PIN_O;
      dvt = dv0 + (uint64_t)(nx * (R_SLOT / 16));
      if (wq == 0) {
        elect_arrive(bempty + 8 * (i & 3));
        if (hf == 0 && n >= 1 && n < 29) {
          const int sl = (n - 1) & 3, m = n + 3;
          mbar_wait(bempty + 8 * sl, ((n - 1) >> 2) & 1);
          elect_load(ring + sl * R_SLOT, g_kv + ((cb * 4 + s * 2 + (m >> 4)) * 16 + (((rb & ~1) + m) & 15)) * 8192, 8192, bfull + 8 * sl, 8192);
        }
        if (wgi == 1 && n == 24) {
          wait_flag_warp(&g_of[(rb * 2) * 32], e1 * 32u);
#pragma unroll
          for (int k = 0; k < 4; k++) elect_load(sb + SM_OG0 + k * 16384, g_o + rb * 131072 + k * 16384, 16384, bar + B_OG0, k ? 0 : 65536);
        }
      }
    }
    const float l0 = __shfl_sync(0xffffffffu, o[8], lane & 28), l1 = __shfl_sync(0xffffffffu, o[10], lane & 28);
    float chk = l0 * 0.f + l1 * 0.f;
#pragma unroll
    for (int i = 0; i < 8; i++) chk = fmaf(o[i], 0.f, chk);
    bad |= !(chk == 0.f);
    const float r0 = 1.0f / l0, r1 = 1.0f / l1;
    uint8_t* odst = g_o + (rb * 32 + rnd * 16 + cb * 2 + s) * 4096 + hf * 2048;
    uint8_t* op = odst + wq * 512 + lane * 4;
    *(uint32_t*)(op) = pack_bf16(o[0] * r0, o[1] * r0);
    *(uint32_t*)(op + 256) = pack_bf16(o[2] * r1, o[3] * r1);
    *(uint32_t*)(op + 128) = pack_bf16(o[4] * r0, o[5] * r0);
    *(uint32_t*)(op + 384) = pack_bf16(o[6] * r1, o[7] * r1);
    if (bar_or(2 + wgi, 128, bad))
      attn_fallback(qf[0], qf[1], qf[2], qf[3], g_kv + (cb * 4 + s * 2 + rnd) * 131072, odst, g_qscr + (b * 4 + wgi) * 512, 2 + wgi);
    __syncwarp();
    if (wq == 0) elect_red_release(&g_of[(rb * 2 + rnd) * 32], 1u);
#pragma unroll
    for (int i = 0; i < 4; i++) qf[i] = qn[i];
  }

  {
    const int row0 = hf * 64 + wq * 16 + g;
    const int col0 = cb * 64 + s * 32 + 2 * t;
    uint32_t xr[8], nr[8];
#pragma unroll
    for (int j = 0; j < 4; j++) {
#pragma unroll
      for (int u = 0; u < 2; u++) {
        const int r = row0 + 8 * u;
        xr[2 * j + u] = __ldg((const uint32_t*)(x + (size_t)(rb * 128 + r) * 512 + col0 + 8 * j));
        nr[2 * j + u] = __ldcg((const uint32_t*)(g_xn + rb * 131072 + cb * 16384 + r * 128 + (((s * 4 + j) ^ (r & 7)) << 4) + t * 4));
      }
    }
    const unsigned key = (unsigned)__ldcg(&g_best);
    float acc2[16];
#pragma unroll
    for (int i = 0; i < 16; i++) acc2[i] = 0.f;
    PIN_ACC16;
    mbar_wait(bar + B_WO, 0);
    mbar_wait(bar + B_OG0, 0);
#pragma unroll
    for (int h2 = 0; h2 < 2; h2++) {
      if (h2 == 1) mbar_wait(bar + B_OG1, 0);
      uint64_t da = mkdesc(sb + (h2 ? SM_OG1 : SM_OG0) + hf * 2048, 128, 256, 0);
      uint64_t db = mkdesc(sb + SM_WO + s * 32768 + h2 * 1024, 4096, 512, 2);
      wg_fence();
#pragma unroll
      for (int k = 0; k < 16; k++) { wg_ss_n32_t(acc2, da, db, 1); DESC_ADD(da, 256); DESC_ADD(db, 128); }
      wg_commit();
      if (h2 == 0) {
        if (warp == 0) {
          wait_flag_warp(&g_of[(rb * 2 + 1) * 32], e1 * 32u);
#pragma unroll
          for (int k = 0; k < 4; k++) elect_load(sb + SM_OG1 + k * 16384, g_o + rb * 131072 + 65536 + k * 16384, 16384, bar + B_OG1, k ? 0 : 65536);
        }
      }
    }
    wg_wait<0>();
    PIN_ACC16;
    const int sel = 2047 - (int)(key & 0xFFFFu) - rb * 128;
    if (sel == row0 || sel == row0 + 8) {
      wait_flag(&g_ffn, e1 * 4u);
      const uint32_t ro = key >> 16;
      const float rv = __uint_as_float(((ro & 0x8000u) ? (ro & 0x7FFFu) : (~ro & 0xFFFFu)) << 16);
      const float sg = bf16r(1.0f / (1.0f + expf(-rv)));
#pragma unroll
      for (int j = 0; j < 4; j++) {
#pragma unroll
        for (int c = 0; c < 2; c++) {
          const int col = col0 + 8 * j + c;
          const float y = bf16r(bf16r(__ldcg(g_y + col) + __ldcg(g_y + 512 + col) + __ldcg(g_y + 1024 + col) + __ldcg(g_y + 1536 + col)) * sg);
          if (sel == row0) acc2[4 * j + c] += y; else acc2[4 * j + 2 + c] += y;
        }
      }
    }
#pragma unroll
    for (int j = 0; j < 4; j++) {
#pragma unroll
      for (int u = 0; u < 2; u++) {
        const float lo = acc2[4 * j + 2 * u] + bf_lo(xr[2 * j + u]) + bf_lo(nr[2 * j + u]);
        const float hi = acc2[4 * j + 2 * u + 1] + bf_hi(xr[2 * j + u]) + bf_hi(nr[2 * j + u]);
        *(uint32_t*)(out + (size_t)(rb * 128 + row0 + 8 * u) * 512 + col0 + 8 * j) = pack_bf16(lo, hi);
      }
    }
  }
}

typedef CUresult (*EncodeFn)(CUtensorMap*, CUtensorMapDataType, cuuint32_t, void*, const cuuint64_t*, const cuuint64_t*,
                             const cuuint32_t*, const cuuint32_t*, CUtensorMapInterleave, CUtensorMapSwizzle,
                             CUtensorMapL2promotion, CUtensorMapFloatOOBfill);

}

extern "C" void kernel_launch(void* const* d_in, const int* in_sizes, int n_in, void* d_out, int out_size) {
  (void)in_sizes; (void)n_in; (void)out_size;
  static EncodeFn encode = nullptr;
  if (!encode) {
    void* fn = nullptr;
    cudaDriverEntryPointQueryResult qr;
    cudaGetDriverEntryPoint("cuTensorMapEncodeTiled", &fn, cudaEnableDefault, &qr);
    encode = (EncodeFn)fn;
    cudaFuncSetAttribute(fused_kernel, cudaFuncAttributeMaxDynamicSharedMemorySize, SM_TOTAL);
  }
  CUtensorMap tm_wqkv, tm_wo;
  {
    const cuuint64_t dims[4] = {32, 512, 3, 16};
    const cuuint64_t strides[3] = {3072, 1024, 64};
    const cuuint32_t box[4] = {32, 64, 3, 2};
    const cuuint32_t es[4] = {1, 1, 1, 1};
    encode(&tm_wqkv, CU_TENSOR_MAP_DATA_TYPE_BFLOAT16, 4, d_in[1], dims, strides, box, es, CU_TENSOR_MAP_INTERLEAVE_NONE,
           CU_TENSOR_MAP_SWIZZLE_64B, CU_TENSOR_MAP_L2_PROMOTION_L2_128B, CU_TENSOR_MAP_FLOAT_OOB_FILL_NONE);
  }
  {
    const cuuint64_t dims[3] = {32, 512, 16};
    const cuuint64_t strides[2] = {1024, 64};
    const cuuint32_t box[3] = {32, 256, 1};
    const cuuint32_t es[3] = {1, 1, 1};
    encode(&tm_wo, CU_TENSOR_MAP_DATA_TYPE_BFLOAT16, 3, d_in[2], dims, strides, box, es, CU_TENSOR_MAP_INTERLEAVE_NONE,
           CU_TENSOR_MAP_SWIZZLE_64B, CU_TENSOR_MAP_L2_PROMOTION_L2_128B, CU_TENSOR_MAP_FLOAT_OOB_FILL_NONE);
  }
  fused_kernel<<<NCTA, 512, SM_TOTAL>>>(tm_wqkv, tm_wo, (const __nv_bfloat16*)d_in[0], (const __nv_bfloat16*)d_in[4],
                                        (const __nv_bfloat16*)d_in[5], (const __nv_bfloat16*)d_in[6],
                                        (const __nv_bfloat16*)d_in[7], (__nv_bfloat16*)d_out);
}
```

```cpp
#include <cuda_runtime.h>
#include <cuda_bf16.h>
#include <cuda.h>
#include <stdint.h>

namespace {

constexpr int NCTA = 132;
constexpr uint32_t A_STAGE = 40960, A_WOFF = 16384;
constexpr uint32_t R_SLOT = 10240, R_STREAM = 61440;
constexpr uint32_t SM_WO = 122880, SM_STASH = 188416, SM_RED = 204800;
constexpr uint32_t SM_AUG = 229376, SM_STAT = 230144, SM_RBAR = 231168, SM_BAR = 231936, SM_MISC = 232192, SM_TOTAL = 232448;
constexpr uint32_t B_FULLA = 0, B_EMPTYA = 40, B_WO = 64;
#define CSYNC 0
#define GATHER_AT 4
#define LN_AFTER -1
#define AWIN 5
constexpr float M_MARGIN = 90.0f;
constexpr float LOG2C = 0.591919f;

__device__ __align__(1024) uint8_t g_kv[32 * 16 * 8192];
__device__ uint4 g_o[16 * 32 * 256];
__device__ uint4 g_rec[2048];
__device__ unsigned long long g_cs[8 * 16 * 192];
__device__ unsigned long long g_y[4 * 512];
__device__ unsigned long long g_sel;
__device__ uint32_t g_qscr[128 * 4 * 512];
__device__ unsigned g_epoch[NCTA * 8];
__device__ uint4 g_flag[128 * 2 * 2];

#define TM(i)
#define TMG(i)
#define PIN_F(x) asm volatile("" : "+f"(x) :: "memory")
#define PIN_R(x) asm volatile("" : "+r"(x) :: "memory")
#define DESC_ADD(d, n) asm volatile("add.s64 %0, %0, " #n ";" : "+l"(d))

__device__ __forceinline__ void wg_fence() { asm volatile("wgmma.fence.sync.aligned;" ::: "memory"); }
__device__ __forceinline__ void wg_commit() { asm volatile("wgmma.commit_group.sync.aligned;" ::: "memory"); }
template <int N> __device__ __forceinline__ void wg_wait() { asm volatile("wgmma.wait_group.sync.aligned %0;" :: "n"(N) : "memory"); }
__device__ __forceinline__ uint64_t mkdesc(uint32_t a, uint32_t lbo, uint32_t sbo, uint32_t swz) {
  return (uint64_t)((a & 0x3FFFF) >> 4) | ((uint64_t)(lbo >> 4) << 16) | ((uint64_t)(sbo >> 4) << 32) | ((uint64_t)swz << 62);
}
__device__ __forceinline__ void mbar_init(uint32_t a, uint32_t c) { asm volatile("mbarrier.init.shared::cta.b64 [%0], %1;" :: "r"(a), "r"(c) : "memory"); }
__device__ __forceinline__ void mbar_wait(uint32_t a, uint32_t ph) {
  asm volatile("{\n.reg .pred p;\n.reg .u32 n;\nmov.u32 n, 0;\n"
               "W: mbarrier.try_wait.parity.shared::cta.b64 p, [%0], %1;\n@p bra.uni D;\n"
               "add.u32 n, n, 1;\nsetp.lt.u32 p, n, 0x400000;\n@p bra.uni W;\ntrap;\nD:\n}" :: "r"(a), "r"(ph) : "memory");
}
__device__ __forceinline__ uint32_t mbar_test(uint32_t a, uint32_t ph) {
  uint32_t ok;
  asm volatile("{\n.reg .pred p;\nmbarrier.test_wait.parity.shared::cta.b64 p, [%1], %2;\nselp.u32 %0, 1, 0, p;\n}" : "=r"(ok) : "r"(a), "r"(ph) : "memory");
  return ok;
}
__device__ __forceinline__ void mbar_wait_if_not(uint32_t ok, uint32_t a, uint32_t ph) {
  asm volatile("{\n.reg .pred p;\n.reg .u32 n;\nsetp.ne.u32 p, %2, 0;\n@p bra.uni D;\nmov.u32 n, 0;\n"
               "W: mbarrier.try_wait.parity.shared::cta.b64 p, [%0], %1;\n@p bra.uni D;\n"
               "add.u32 n, n, 1;\nsetp.lt.u32 p, n, 0x400000;\n@p bra.uni W;\ntrap;\nD:\n}" :: "r"(a), "r"(ph), "r"(ok) : "memory");
}
__device__ __forceinline__ void wait_flag_warp(const unsigned* p, unsigned target) {
  asm volatile("{\n.reg .pred p;\n.reg .u32 n, v;\nmov.u32 n, 0;\n"
               "W: ld.relaxed.gpu.global.u32 v, [%0];\nsub.s32 v, v, %1;\nsetp.ge.s32 p, v, 0;\nvote.sync.all.pred p, p, 0xffffffff;\n@p bra.uni D;\n"
               "add.u32 n, n, 1;\nsetp.lt.u32 p, n, 0x400000;\n@p bra.uni W;\ntrap;\n"
               "D: fence.acquire.gpu;\nfence.proxy.async.global;\n}" :: "l"(p), "r"(target) : "memory");
}
__device__ __forceinline__ void st_tag64(unsigned long long* p, uint32_t v, uint32_t tag) {
  asm volatile("{\n.reg .b64 r;\nmov.b64 r, {%1, %2};\nst.relaxed.gpu.global.b64 [%0], r;\n}" :: "l"(p), "r"(v), "r"(tag) : "memory");
}
__device__ __forceinline__ void st_rec(uint4* p, uint32_t a, uint32_t b, uint32_t c, uint32_t tag) {
  asm volatile("{\n.reg .b64 lo, hi;\n.reg .b128 r;\nmov.b64 lo, {%1, %2};\nmov.b64 hi, {%3, %4};\nmov.b128 r, {lo, hi};\n"
               "st.relaxed.gpu.global.b128 [%0], r;\n}" :: "l"(p), "r"(a), "r"(b), "r"(c), "r"(tag) : "memory");
}
__device__ __forceinline__ uint4 ld_rec(const uint4* p) {
  uint4 v;
  asm volatile("{\n.reg .b64 lo, hi;\n.reg .b128 r;\nld.relaxed.gpu.global.b128 r, [%4];\nmov.b128 {lo, hi}, r;\nmov.b64 {%0, %1}, lo;\nmov.b64 {%2, %3}, hi;\n}"
               : "=r"(v.x), "=r"(v.y), "=r"(v.z), "=r"(v.w) : "l"(p) : "memory");
  return v;
}
__device__ __forceinline__ void wait_rec(uint4& v, const uint4* p, uint32_t tag) {
  asm volatile("{\n.reg .pred p;\n.reg .u32 n;\n.reg .b64 lo, hi;\n.reg .b128 r;\nmov.u32 n, 0;\n"
               "W: setp.eq.u32 p, %3, %5;\nvote.sync.all.pred p, p, 0xffffffff;\n@p bra.uni D;\n"
               "ld.relaxed.gpu.global.b128 r, [%4];\nmov.b128 {lo, hi}, r;\nmov.b64 {%0, %1}, lo;\nmov.b64 {%2, %3}, hi;\n"
               "add.u32 n, n, 1;\nsetp.lt.u32 p, n, 0x400000;\n@p bra.uni W;\ntrap;\nD:\n}"
               : "+r"(v.x), "+r"(v.y), "+r"(v.z), "+r"(v.w) : "l"(p), "r"(tag) : "memory");
}
__device__ __forceinline__ uint2 ld_tag64(const unsigned long long* p) {
  uint2 v;
  asm volatile("{\n.reg .b64 r;\nld.relaxed.gpu.global.b64 r, [%2];\nmov.b64 {%0, %1}, r;\n}" : "=r"(v.x), "=r"(v.y) : "l"(p) : "memory");
  return v;
}
__device__ __forceinline__ uint32_t wait_tag64(uint2 v, const unsigned long long* p, uint32_t tag) {
  asm volatile("{\n.reg .pred p;\n.reg .u32 n;\n.reg .b64 r;\nmov.u32 n, 0;\n"
               "W: setp.eq.u32 p, %1, %3;\nvote.sync.all.pred p, p, 0xffffffff;\n@p bra.uni D;\n"
               "ld.relaxed.gpu.global.b64 r, [%2];\nmov.b64 {%0, %1}, r;\n"
               "add.u32 n, n, 1;\nsetp.lt.u32 p, n, 0x400000;\n@p bra.uni W;\ntrap;\nD:\n}" : "+r"(v.x), "+r"(v.y) : "l"(p), "r"(tag) : "memory");
  return v.x;
}
__device__ __forceinline__ void elect_load2(uint32_t d0, const void* s0, uint32_t d1, const void* s1, uint32_t bytes, uint32_t bar, uint32_t expect) {
  asm volatile("{\n.reg .pred p, q;\nelect.sync _|p, 0xffffffff;\nsetp.ne.and.u32 q, %6, 0, p;\n"
               "@q mbarrier.arrive.expect_tx.shared::cta.b64 _, [%5], %6;\n"
               "@p cp.async.bulk.shared::cluster.global.mbarrier::complete_tx::bytes [%0], [%1], %4, [%5];\n"
               "@p cp.async.bulk.shared::cluster.global.mbarrier::complete_tx::bytes [%2], [%3], %4, [%5];\n}"
               :: "r"(d0), "l"(s0), "r"(d1), "l"(s1), "r"(bytes), "r"(bar), "r"(expect) : "memory");
}
__device__ __forceinline__ void elect_load3(uint32_t d, const void* s0, const void* s1, const void* s2, uint32_t bar) {
  asm volatile("{\n.reg .pred p;\n.reg .u32 d1, d2;\nelect.sync _|p, 0xffffffff;\nadd.u32 d1, %0, 10240;\nadd.u32 d2, %0, 20480;\n"
               "@p mbarrier.arrive.expect_tx.shared::cta.b64 _, [%4], 24576;\n"
               "@p cp.async.bulk.shared::cluster.global.mbarrier::complete_tx::bytes [%0], [%1], 8192, [%4];\n"
               "@p cp.async.bulk.shared::cluster.global.mbarrier::complete_tx::bytes [d1], [%2], 8192, [%4];\n"
               "@p cp.async.bulk.shared::cluster.global.mbarrier::complete_tx::bytes [d2], [%3], 8192, [%4];\n}"
               :: "r"(d), "l"(s0), "l"(s1), "l"(s2), "r"(bar) : "memory");
}
__device__ __forceinline__ void elect_load_ax(uint32_t dst, const CUtensorMap* mw, const CUtensorMap* mx, int k0, int cg, int row, uint32_t bar) {
  asm volatile("{\n.reg .pred p;\n.reg .u32 d;\nelect.sync _|p, 0xffffffff;\nadd.u32 d, %0, 16384;\n"
               "@p mbarrier.arrive.expect_tx.shared::cta.b64 _, [%6], 40960;\n"
               "@p cp.async.bulk.tensor.2d.shared::cluster.global.mbarrier::complete_tx::bytes [%0], [%2, {%3, %5}], [%6];\n"
               "@p cp.async.bulk.tensor.3d.shared::cluster.global.mbarrier::complete_tx::bytes [d], [%1, {%4, %3, 0}], [%6];\n}"
               :: "r"(dst), "l"(mw), "l"(mx), "r"(k0), "r"(cg), "r"(row), "r"(bar) : "memory");
}
__device__ __forceinline__ void elect_tma2d(uint32_t dst, const CUtensorMap* m, int c1, int c2, uint32_t bar, uint32_t expect) {
  asm volatile("{\n.reg .pred p, q;\nelect.sync _|p, 0xffffffff;\nsetp.ne.and.u32 q, %5, 0, p;\n"
               "@q mbarrier.arrive.expect_tx.shared::cta.b64 _, [%4], %5;\n"
               "@p cp.async.bulk.tensor.2d.shared::cluster.global.mbarrier::complete_tx::bytes [%0], [%1, {%2, %3}], [%4];\n}"
               :: "r"(dst), "l"(m), "r"(c1), "r"(c2), "r"(bar), "r"(expect) : "memory");
}
__device__ __forceinline__ void arrive_if(uint32_t a, uint32_t pred) {
  asm volatile("{\n.reg .pred p;\nsetp.ne.u32 p, %1, 0;\n@p mbarrier.arrive.shared::cta.b64 _, [%0];\n}" :: "r"(a), "r"(pred) : "memory");
}
__device__ __forceinline__ void fence_async_smem() { asm volatile("fence.proxy.async.shared::cta;" ::: "memory"); }
__device__ __forceinline__ void bar_sync(int id, int n) { asm volatile("bar.sync %0, %1;" :: "r"(id), "r"(n) : "memory"); }
__device__ __forceinline__ void bar_arrive(int id, int n) { asm volatile("bar.arrive %0, %1;" :: "r"(id), "r"(n) : "memory"); }
__device__ __forceinline__ uint32_t pack_bf16(float lo, float hi) { uint32_t r; asm("cvt.rn.bf16x2.f32 %0, %1, %2;" : "=r"(r) : "f"(hi), "f"(lo)); return r; }
__device__ __forceinline__ float bf16r(float x) { return __uint_as_float(pack_bf16(0.f, x) & 0xFFFF0000u); }
__device__ __forceinline__ float bf_lo(uint32_t v) { return __uint_as_float(v << 16); }
__device__ __forceinline__ float bf_hi(uint32_t v) { return __uint_as_float(v & 0xFFFF0000u); }
__device__ __forceinline__ uint32_t nonzero(uint32_t v) { return v ? v : 0x80000000u; }
__device__ __forceinline__ float ex2(float x) { float y; asm("ex2.approx.ftz.f32 %0, %1;" : "=f"(y) : "f"(x)); return y; }
__device__ __forceinline__ void sts32(uint32_t a, uint32_t v) { asm volatile("st.shared.u32 [%0], %1;" :: "r"(a), "r"(v) : "memory"); }
__device__ __forceinline__ void sts128(uint32_t a, uint32_t x, uint32_t y, uint32_t z, uint32_t w) {
  asm volatile("st.shared.v4.u32 [%0], {%1,%2,%3,%4};" :: "r"(a), "r"(x), "r"(y), "r"(z), "r"(w) : "memory");
}
__device__ __forceinline__ uint4 lds128(uint32_t a) {
  uint4 v; asm volatile("ld.shared.v4.u32 {%0,%1,%2,%3}, [%4];" : "=r"(v.x), "=r"(v.y), "=r"(v.z), "=r"(v.w) : "r"(a) : "memory"); return v;
}
__device__ __forceinline__ void stsm4(uint32_t a, uint32_t x, uint32_t y, uint32_t z, uint32_t w) {
  asm volatile("stmatrix.sync.aligned.m8n8.x4.shared.b16 [%0], {%1,%2,%3,%4};" :: "r"(a), "r"(x), "r"(y), "r"(z), "r"(w) : "memory");
}
__device__ __forceinline__ uint32_t ld_nc32(const void* p) {
  uint32_t v; asm volatile("ld.global.nc.u32 %0, [%1];" : "=r"(v) : "l"(p) : "memory"); return v;
}
__device__ __forceinline__ uint4 ld_nc128(const void* p) {
  uint4 v; asm volatile("ld.global.nc.v4.u32 {%0,%1,%2,%3}, [%4];" : "=r"(v.x), "=r"(v.y), "=r"(v.z), "=r"(v.w) : "l"(p) : "memory"); return v;
}
__device__ __forceinline__ unsigned ld_relaxed(const unsigned* p) {
  unsigned v; asm volatile("ld.relaxed.gpu.global.u32 %0, [%1];" : "=r"(v) : "l"(p) : "memory"); return v;
}
__device__ __forceinline__ void ld_frag(uint32_t* a, const uint4* p) {
  asm volatile("ld.relaxed.gpu.global.v4.u32 {%0,%1,%2,%3}, [%4];" : "=r"(a[0]), "=r"(a[1]), "=r"(a[2]), "=r"(a[3]) : "l"(p) : "memory");
}

__device__ __forceinline__ uint32_t exp2_pair_mufu(float a, float b) { return pack_bf16(ex2(a), ex2(b)); }
__device__ __forceinline__ uint32_t exp2_pair_fma(float a, float b, float c, uint32_t kmant, uint32_t kexpo) {
  float z0, z1;
  uint32_t t, v, e, r;
  asm("fma.rn.f32 %0, %1, 0f00000080, %2;" : "=f"(z0) : "f"(a), "f"(c));
  asm("fma.rn.f32 %0, %1, 0f00000080, %2;" : "=f"(z1) : "f"(b), "f"(c));
  asm("cvt.pack.sat.s16.s32 %0, %1, %2;" : "=r"(t) : "r"(__float_as_uint(z1)), "r"(__float_as_uint(z0)));
  asm("lop3.b32 %0, %1, 0x007F007F, %2, 0xEA;" : "=r"(v) : "r"(t), "r"(kmant));
  asm("lop3.b32 %0, %1, 0x7F807F80, %2, 0xEA;" : "=r"(e) : "r"(t), "r"(kexpo));
  asm("fma.rn.bf16x2 %0, %1, %2, %3;" : "=r"(r) : "r"(t), "r"(v), "r"(e));
  return r;
}

__device__ __forceinline__ void wait_frags(uint32_t* a, const uint4* p) {
  asm volatile("{\n.reg .pred p;\n.reg .u32 n, m<8>, a, b;\nmov.u32 n, 0;\nW:\n"
    "min.u32 a, %0, %1;\nmin.u32 b, %2, %3;\nmin.u32 m0, a, b;\n"
    "min.u32 a, %4, %5;\nmin.u32 b, %6, %7;\nmin.u32 m1, a, b;\n"
    "min.u32 a, %8, %9;\nmin.u32 b, %10, %11;\nmin.u32 m2, a, b;\n"
    "min.u32 a, %12, %13;\nmin.u32 b, %14, %15;\nmin.u32 m3, a, b;\n"
    "min.u32 a, %16, %17;\nmin.u32 b, %18, %19;\nmin.u32 m4, a, b;\n"
    "min.u32 a, %20, %21;\nmin.u32 b, %22, %23;\nmin.u32 m5, a, b;\n"
    "min.u32 a, %24, %25;\nmin.u32 b, %26, %27;\nmin.u32 m6, a, b;\n"
    "min.u32 a, %28, %29;\nmin.u32 b, %30, %31;\nmin.u32 m7, a, b;\n"
    "min.u32 a, m0, m1;\nmin.u32 a, a, m2;\nmin.u32 a, a, m3;\nmin.u32 b, m4, m5;\nmin.u32 b, b, m6;\nmin.u32 b, b, m7;\nmin.u32 a, a, b;\n"
    "setp.ne.u32 p, a, 0;\nvote.sync.all.pred p, p, 0xffffffff;\n@p bra.uni D;\n"
    "setp.eq.u32 p, m0, 0;\n@p ld.relaxed.gpu.global.v4.u32 {%0,%1,%2,%3}, [%32 + 0];\n"
    "setp.eq.u32 p, m1, 0;\n@p ld.relaxed.gpu.global.v4.u32 {%4,%5,%6,%7}, [%32 + 16384];\n"
    "setp.eq.u32 p, m2, 0;\n@p ld.relaxed.gpu.global.v4.u32 {%8,%9,%10,%11}, [%32 + 32768];\n"
    "setp.eq.u32 p, m3, 0;\n@p ld.relaxed.gpu.global.v4.u32 {%12,%13,%14,%15}, [%32 + 49152];\n"
    "setp.eq.u32 p, m4, 0;\n@p ld.relaxed.gpu.global.v4.u32 {%16,%17,%18,%19}, [%32 + 65536];\n"
    "setp.eq.u32 p, m5, 0;\n@p ld.relaxed.gpu.global.v4.u32 {%20,%21,%22,%23}, [%32 + 81920];\n"
    "setp.eq.u32 p, m6, 0;\n@p ld.relaxed.gpu.global.v4.u32 {%24,%25,%26,%27}, [%32 + 98304];\n"
    "setp.eq.u32 p, m7, 0;\n@p ld.relaxed.gpu.global.v4.u32 {%28,%29,%30,%31}, [%32 + 114688];\n"
    "add.u32 n, n, 1;\nsetp.lt.u32 p, n, 0x200000;\n@p bra.uni W;\ntrap;\nD:\n}"
    : "+r"(a[0]),"+r"(a[1]),"+r"(a[2]),"+r"(a[3]),"+r"(a[4]),"+r"(a[5]),"+r"(a[6]),"+r"(a[7]),"+r"(a[8]),"+r"(a[9]),"+r"(a[10]),"+r"(a[11]),"+r"(a[12]),"+r"(a[13]),"+r"(a[14]),"+r"(a[15]),"+r"(a[16]),"+r"(a[17]),"+r"(a[18]),"+r"(a[19]),"+r"(a[20]),"+r"(a[21]),"+r"(a[22]),"+r"(a[23]),"+r"(a[24]),"+r"(a[25]),"+r"(a[26]),"+r"(a[27]),"+r"(a[28]),"+r"(a[29]),"+r"(a[30]),"+r"(a[31])
    : "l"(p) : "memory");
}
__device__ __forceinline__ void ld_cs(uint32_t* a, const unsigned long long* p) {
  asm volatile("{\n.reg .b64 a, b;\n"
    "ld.relaxed.gpu.global.b64 a, [%32 + 0];\nmov.b64 {%0, %1}, a;\n"
    "ld.relaxed.gpu.global.b64 a, [%32 + 1536];\nmov.b64 {%2, %3}, a;\n"
    "ld.relaxed.gpu.global.b64 a, [%32 + 3072];\nmov.b64 {%4, %5}, a;\n"
    "ld.relaxed.gpu.global.b64 a, [%32 + 4608];\nmov.b64 {%6, %7}, a;\n"
    "ld.relaxed.gpu.global.b64 a, [%32 + 6144];\nmov.b64 {%8, %9}, a;\n"
    "ld.relaxed.gpu.global.b64 a, [%32 + 7680];\nmov.b64 {%10, %11}, a;\n"
    "ld.relaxed.gpu.global.b64 a, [%32 + 9216];\nmov.b64 {%12, %13}, a;\n"
    "ld.relaxed.gpu.global.b64 a, [%32 + 10752];\nmov.b64 {%14, %15}, a;\n"
    "ld.relaxed.gpu.global.b64 a, [%32 + 12288];\nmov.b64 {%16, %17}, a;\n"
    "ld.relaxed.gpu.global.b64 a, [%32 + 13824];\nmov.b64 {%18, %19}, a;\n"
    "ld.relaxed.gpu.global.b64 a, [%32 + 15360];\nmov.b64 {%20, %21}, a;\n"
    "ld.relaxed.gpu.global.b64 a, [%32 + 16896];\nmov.b64 {%22, %23}, a;\n"
    "ld.relaxed.gpu.global.b64 a, [%32 + 18432];\nmov.b64 {%24, %25}, a;\n"
    "ld.relaxed.gpu.global.b64 a, [%32 + 19968];\nmov.b64 {%26, %27}, a;\n"
    "ld.relaxed.gpu.global.b64 a, [%32 + 21504];\nmov.b64 {%28, %29}, a;\n"
    "ld.relaxed.gpu.global.b64 a, [%32 + 23040];\nmov.b64 {%30, %31}, a;\n"
    "}"
    : "=r"(a[0]),"=r"(a[1]),"=r"(a[2]),"=r"(a[3]),"=r"(a[4]),"=r"(a[5]),"=r"(a[6]),"=r"(a[7]),"=r"(a[8]),"=r"(a[9]),"=r"(a[10]),"=r"(a[11]),"=r"(a[12]),"=r"(a[13]),"=r"(a[14]),"=r"(a[15]),"=r"(a[16]),"=r"(a[17]),"=r"(a[18]),"=r"(a[19]),"=r"(a[20]),"=r"(a[21]),"=r"(a[22]),"=r"(a[23]),"=r"(a[24]),"=r"(a[25]),"=r"(a[26]),"=r"(a[27]),"=r"(a[28]),"=r"(a[29]),"=r"(a[30]),"=r"(a[31]) : "l"(p) : "memory");
}
__device__ __forceinline__ void wait_cs(uint32_t* a, const unsigned long long* p, uint32_t tag) {
  asm volatile("{\n.reg .b64 a, b;\n.reg .pred p;\n.reg .u32 n;\nmov.u32 n, 0;\nW: setp.eq.u32 p, n, n;\n"
    "setp.eq.and.u32 p, %1, %33, p;\n"
    "setp.eq.and.u32 p, %3, %33, p;\n"
    "setp.eq.and.u32 p, %5, %33, p;\n"
    "setp.eq.and.u32 p, %7, %33, p;\n"
    "setp.eq.and.u32 p, %9, %33, p;\n"
    "setp.eq.and.u32 p, %11, %33, p;\n"
    "setp.eq.and.u32 p, %13, %33, p;\n"
    "setp.eq.and.u32 p, %15, %33, p;\n"
    "setp.eq.and.u32 p, %17, %33, p;\n"
    "setp.eq.and.u32 p, %19, %33, p;\n"
    "setp.eq.and.u32 p, %21, %33, p;\n"
    "setp.eq.and.u32 p, %23, %33, p;\n"
    "setp.eq.and.u32 p, %25, %33, p;\n"
    "setp.eq.and.u32 p, %27, %33, p;\n"
    "setp.eq.and.u32 p, %29, %33, p;\n"
    "setp.eq.and.u32 p, %31, %33, p;\n"
    "vote.sync.all.pred p, p, 0xffffffff;\n@p bra.uni D;\n"
    "ld.relaxed.gpu.global.b64 a, [%32 + 0];\nmov.b64 {%0, %1}, a;\n"
    "ld.relaxed.gpu.global.b64 a, [%32 + 1536];\nmov.b64 {%2, %3}, a;\n"
    "ld.relaxed.gpu.global.b64 a, [%32 + 3072];\nmov.b64 {%4, %5}, a;\n"
    "ld.relaxed.gpu.global.b64 a, [%32 + 4608];\nmov.b64 {%6, %7}, a;\n"
    "ld.relaxed.gpu.global.b64 a, [%32 + 6144];\nmov.b64 {%8, %9}, a;\n"
    "ld.relaxed.gpu.global.b64 a, [%32 + 7680];\nmov.b64 {%10, %11}, a;\n"
    "ld.relaxed.gpu.global.b64 a, [%32 + 9216];\nmov.b64 {%12, %13}, a;\n"
    "ld.relaxed.gpu.global.b64 a, [%32 + 10752];\nmov.b64 {%14, %15}, a;\n"
    "ld.relaxed.gpu.global.b64 a, [%32 + 12288];\nmov.b64 {%16, %17}, a;\n"
    "ld.relaxed.gpu.global.b64 a, [%32 + 13824];\nmov.b64 {%18, %19}, a;\n"
    "ld.relaxed.gpu.global.b64 a, [%32 + 15360];\nmov.b64 {%20, %21}, a;\n"
    "ld.relaxed.gpu.global.b64 a, [%32 + 16896];\nmov.b64 {%22, %23}, a;\n"
    "ld.relaxed.gpu.global.b64 a, [%32 + 18432];\nmov.b64 {%24, %25}, a;\n"
    "ld.relaxed.gpu.global.b64 a, [%32 + 19968];\nmov.b64 {%26, %27}, a;\n"
    "ld.relaxed.gpu.global.b64 a, [%32 + 21504];\nmov.b64 {%28, %29}, a;\n"
    "ld.relaxed.gpu.global.b64 a, [%32 + 23040];\nmov.b64 {%30, %31}, a;\n"
    "add.u32 n, n, 1;\nsetp.lt.u32 p, n, 0x200000;\n@p bra.uni W;\ntrap;\nD:\n}"
    : "+r"(a[0]),"+r"(a[1]),"+r"(a[2]),"+r"(a[3]),"+r"(a[4]),"+r"(a[5]),"+r"(a[6]),"+r"(a[7]),"+r"(a[8]),"+r"(a[9]),"+r"(a[10]),"+r"(a[11]),"+r"(a[12]),"+r"(a[13]),"+r"(a[14]),"+r"(a[15]),"+r"(a[16]),"+r"(a[17]),"+r"(a[18]),"+r"(a[19]),"+r"(a[20]),"+r"(a[21]),"+r"(a[22]),"+r"(a[23]),"+r"(a[24]),"+r"(a[25]),"+r"(a[26]),"+r"(a[27]),"+r"(a[28]),"+r"(a[29]),"+r"(a[30]),"+r"(a[31]) : "l"(p), "r"(tag) : "memory");
}
__device__ __forceinline__ void wg_ss_n192_t(float* d, uint64_t da, uint64_t db, int sd) {
  asm volatile("{\n.reg .pred p;\nsetp.ne.b32 p, %98, 0;\n"
    "wgmma.mma_async.sync.aligned.m64n192k16.f32.bf16.bf16 {%0,%1,%2,%3,%4,%5,%6,%7,%8,%9,%10,%11,%12,%13,%14,%15,%16,%17,%18,%19,%20,%21,%22,%23,%24,%25,%26,%27,%28,%29,%30,%31,%32,%33,%34,%35,%36,%37,%38,%39,%40,%41,%42,%43,%44,%45,%46,%47,%48,%49,%50,%51,%52,%53,%54,%55,%56,%57,%58,%59,%60,%61,%62,%63,%64,%65,%66,%67,%68,%69,%70,%71,%72,%73,%74,%75,%76,%77,%78,%79,%80,%81,%82,%83,%84,%85,%86,%87,%88,%89,%90,%91,%92,%93,%94,%95}, %96, %97, p, 1, 1, 0, 1;\n}\n"
    : "+f"(d[0]),"+f"(d[1]),"+f"(d[2]),"+f"(d[3]),"+f"(d[4]),"+f"(d[5]),"+f"(d[6]),"+f"(d[7]),"+f"(d[8]),"+f"(d[9]),"+f"(d[10]),"+f"(d[11]),"+f"(d[12]),"+f"(d[13]),"+f"(d[14]),"+f"(d[15]),"+f"(d[16]),"+f"(d[17]),"+f"(d[18]),"+f"(d[19]),"+f"(d[20]),"+f"(d[21]),"+f"(d[22]),"+f"(d[23]),"+f"(d[24]),"+f"(d[25]),"+f"(d[26]),"+f"(d[27]),"+f"(d[28]),"+f"(d[29]),"+f"(d[30]),"+f"(d[31]),"+f"(d[32]),"+f"(d[33]),"+f"(d[34]),"+f"(d[35]),"+f"(d[36]),"+f"(d[37]),"+f"(d[38]),"+f"(d[39]),"+f"(d[40]),"+f"(d[41]),"+f"(d[42]),"+f"(d[43]),"+f"(d[44]),"+f"(d[45]),"+f"(d[46]),"+f"(d[47]),"+f"(d[48]),"+f"(d[49]),"+f"(d[50]),"+f"(d[51]),"+f"(d[52]),"+f"(d[53]),"+f"(d[54]),"+f"(d[55]),"+f"(d[56]),"+f"(d[57]),"+f"(d[58]),"+f"(d[59]),"+f"(d[60]),"+f"(d[61]),"+f"(d[62]),"+f"(d[63]),"+f"(d[64]),"+f"(d[65]),"+f"(d[66]),"+f"(d[67]),"+f"(d[68]),"+f"(d[69]),"+f"(d[70]),"+f"(d[71]),"+f"(d[72]),"+f"(d[73]),"+f"(d[74]),"+f"(d[75]),"+f"(d[76]),"+f"(d[77]),"+f"(d[78]),"+f"(d[79]),"+f"(d[80]),"+f"(d[81]),"+f"(d[82]),"+f"(d[83]),"+f"(d[84]),"+f"(d[85]),"+f"(d[86]),"+f"(d[87]),"+f"(d[88]),"+f"(d[89]),"+f"(d[90]),"+f"(d[91]),"+f"(d[92]),"+f"(d[93]),"+f"(d[94]),"+f"(d[95])
    : "l"(da), "l"(db), "r"(sd));
}
__device__ __forceinline__ void wg_rs_n32_t(float* d, const uint32_t* a, uint64_t db, int sd) {
  asm volatile("{\n.reg .pred p;\nsetp.ne.b32 p, %21, 0;\n"
    "wgmma.mma_async.sync.aligned.m64n32k16.f32.bf16.bf16 {%0,%1,%2,%3,%4,%5,%6,%7,%8,%9,%10,%11,%12,%13,%14,%15}, {%16,%17,%18,%19}, %20, p, 1, 1, 1;\n}\n"
    : "+f"(d[0]),"+f"(d[1]),"+f"(d[2]),"+f"(d[3]),"+f"(d[4]),"+f"(d[5]),"+f"(d[6]),"+f"(d[7]),"+f"(d[8]),"+f"(d[9]),"+f"(d[10]),"+f"(d[11]),"+f"(d[12]),"+f"(d[13]),"+f"(d[14]),"+f"(d[15])
    : "r"(a[0]),"r"(a[1]),"r"(a[2]),"r"(a[3]), "l"(db), "r"(sd));
}
__device__ __forceinline__ void wg_rs_n192(float* d, const uint32_t* a, uint64_t db, int sd) {
  asm volatile("{\n.reg .pred p;\nsetp.ne.b32 p, %101, 0;\n"
    "wgmma.mma_async.sync.aligned.m64n192k16.f32.bf16.bf16 {%0,%1,%2,%3,%4,%5,%6,%7,%8,%9,%10,%11,%12,%13,%14,%15,%16,%17,%18,%19,%20,%21,%22,%23,%24,%25,%26,%27,%28,%29,%30,%31,%32,%33,%34,%35,%36,%37,%38,%39,%40,%41,%42,%43,%44,%45,%46,%47,%48,%49,%50,%51,%52,%53,%54,%55,%56,%57,%58,%59,%60,%61,%62,%63,%64,%65,%66,%67,%68,%69,%70,%71,%72,%73,%74,%75,%76,%77,%78,%79,%80,%81,%82,%83,%84,%85,%86,%87,%88,%89,%90,%91,%92,%93,%94,%95}, {%96,%97,%98,%99}, %100, p, 1, 1, 0;\n}\n"
    : "+f"(d[0]),"+f"(d[1]),"+f"(d[2]),"+f"(d[3]),"+f"(d[4]),"+f"(d[5]),"+f"(d[6]),"+f"(d[7]),"+f"(d[8]),"+f"(d[9]),"+f"(d[10]),"+f"(d[11]),"+f"(d[12]),"+f"(d[13]),"+f"(d[14]),"+f"(d[15]),"+f"(d[16]),"+f"(d[17]),"+f"(d[18]),"+f"(d[19]),"+f"(d[20]),"+f"(d[21]),"+f"(d[22]),"+f"(d[23]),"+f"(d[24]),"+f"(d[25]),"+f"(d[26]),"+f"(d[27]),"+f"(d[28]),"+f"(d[29]),"+f"(d[30]),"+f"(d[31]),"+f"(d[32]),"+f"(d[33]),"+f"(d[34]),"+f"(d[35]),"+f"(d[36]),"+f"(d[37]),"+f"(d[38]),"+f"(d[39]),"+f"(d[40]),"+f"(d[41]),"+f"(d[42]),"+f"(d[43]),"+f"(d[44]),"+f"(d[45]),"+f"(d[46]),"+f"(d[47]),"+f"(d[48]),"+f"(d[49]),"+f"(d[50]),"+f"(d[51]),"+f"(d[52]),"+f"(d[53]),"+f"(d[54]),"+f"(d[55]),"+f"(d[56]),"+f"(d[57]),"+f"(d[58]),"+f"(d[59]),"+f"(d[60]),"+f"(d[61]),"+f"(d[62]),"+f"(d[63]),"+f"(d[64]),"+f"(d[65]),"+f"(d[66]),"+f"(d[67]),"+f"(d[68]),"+f"(d[69]),"+f"(d[70]),"+f"(d[71]),"+f"(d[72]),"+f"(d[73]),"+f"(d[74]),"+f"(d[75]),"+f"(d[76]),"+f"(d[77]),"+f"(d[78]),"+f"(d[79]),"+f"(d[80]),"+f"(d[81]),"+f"(d[82]),"+f"(d[83]),"+f"(d[84]),"+f"(d[85]),"+f"(d[86]),"+f"(d[87]),"+f"(d[88]),"+f"(d[89]),"+f"(d[90]),"+f"(d[91]),"+f"(d[92]),"+f"(d[93]),"+f"(d[94]),"+f"(d[95])
    : "r"(a[0]),"r"(a[1]),"r"(a[2]),"r"(a[3]), "l"(db), "r"(sd));
}
__device__ __forceinline__ void wg_rs_n24(float* d, const uint32_t* a, uint64_t db, int sd) {
  asm volatile("{\n.reg .pred p;\nsetp.ne.b32 p, %17, 0;\n"
    "wgmma.mma_async.sync.aligned.m64n24k16.f32.bf16.bf16 {%0,%1,%2,%3,%4,%5,%6,%7,%8,%9,%10,%11}, {%12,%13,%14,%15}, %16, p, 1, 1, 0;\n}\n"
    : "+f"(d[0]),"+f"(d[1]),"+f"(d[2]),"+f"(d[3]),"+f"(d[4]),"+f"(d[5]),"+f"(d[6]),"+f"(d[7]),"+f"(d[8]),"+f"(d[9]),"+f"(d[10]),"+f"(d[11])
    : "r"(a[0]),"r"(a[1]),"r"(a[2]),"r"(a[3]), "l"(db), "r"(sd));
}
__device__ __forceinline__ void wg_rs_n40(float* d, const uint32_t* a, uint64_t db, int sd) {
  asm volatile("{\n.reg .pred p;\nsetp.ne.b32 p, %25, 0;\n"
    "wgmma.mma_async.sync.aligned.m64n40k16.f32.bf16.bf16 {%0,%1,%2,%3,%4,%5,%6,%7,%8,%9,%10,%11,%12,%13,%14,%15,%16,%17,%18,%19}, {%20,%21,%22,%23}, %24, p, 1, 1, 0;\n}\n"
    : "+f"(d[0]),"+f"(d[1]),"+f"(d[2]),"+f"(d[3]),"+f"(d[4]),"+f"(d[5]),"+f"(d[6]),"+f"(d[7]),"+f"(d[8]),"+f"(d[9]),"+f"(d[10]),"+f"(d[11]),"+f"(d[12]),"+f"(d[13]),"+f"(d[14]),"+f"(d[15]),"+f"(d[16]),"+f"(d[17]),"+f"(d[18]),"+f"(d[19])
    : "r"(a[0]),"r"(a[1]),"r"(a[2]),"r"(a[3]), "l"(db), "r"(sd));
}
__device__ __forceinline__ void wg_rs_n24_t(float* d, const uint32_t* a, uint64_t db, int sd) {
  asm volatile("{\n.reg .pred p;\nsetp.ne.b32 p, %17, 0;\n"
    "wgmma.mma_async.sync.aligned.m64n24k16.f32.bf16.bf16 {%0,%1,%2,%3,%4,%5,%6,%7,%8,%9,%10,%11}, {%12,%13,%14,%15}, %16, p, 1, 1, 1;\n}\n"
    : "+f"(d[0]),"+f"(d[1]),"+f"(d[2]),"+f"(d[3]),"+f"(d[4]),"+f"(d[5]),"+f"(d[6]),"+f"(d[7]),"+f"(d[8]),"+f"(d[9]),"+f"(d[10]),"+f"(d[11])
    : "r"(a[0]),"r"(a[1]),"r"(a[2]),"r"(a[3]), "l"(db), "r"(sd));
}
#define KPERM 0x72651430u
#define NMUFU 24
#define QK_S0 do { \
  wg_fence(); \
  wg_rs_n24(s0, qa, daug, 0); wg_rs_n24(s0, qf, dkt, 1); DESC_ADD(dkt, 48); \
  wg_rs_n40(s0 + 12, qf, dkt, 0); DESC_ADD(dkt, 80); \
  wg_commit(); \
} while (0)
#define EXP_PV_S0 do { \
  pr[0] = exp2_pair_mufu(s0[0], s0[1]); \
  pr[1] = exp2_pair_mufu(s0[2], s0[3]); \
  pr[2] = exp2_pair_fma(s0[12], s0[13], c0, kmant, kexpo); \
  pr[3] = exp2_pair_fma(s0[14], s0[15], c1, kmant, kexpo); \
  pr[4] = exp2_pair_fma(s0[16], s0[17], c0, kmant, kexpo); \
  pr[5] = exp2_pair_fma(s0[18], s0[19], c1, kmant, kexpo); \
  pr[6] = exp2_pair_mufu(s0[4], s0[5]); \
  pr[7] = exp2_pair_mufu(s0[6], s0[7]); \
  PIN_R(pr[0]); \
  PIN_R(pr[1]); \
  PIN_R(pr[2]); \
  PIN_R(pr[3]); \
  PIN_R(pr[4]); \
  PIN_R(pr[5]); \
  PIN_R(pr[6]); \
  PIN_R(pr[7]); \
  wg_fence(); \
  wg_rs_n24_t(o, pr + 0, dvt, 1); DESC_ADD(dvt, 16); \
  wg_rs_n24_t(o, pr + 4, dvt, 1); DESC_ADD(dvt, 16); \
  pr[8] = exp2_pair_fma(s0[20], s0[21], c0, kmant, kexpo); \
  pr[9] = exp2_pair_fma(s0[22], s0[23], c1, kmant, kexpo); \
  pr[10] = exp2_pair_fma(s0[24], s0[25], c0, kmant, kexpo); \
  pr[11] = exp2_pair_fma(s0[26], s0[27], c1, kmant, kexpo); \
  pr[12] = exp2_pair_mufu(s0[8], s0[9]); \
  pr[13] = exp2_pair_mufu(s0[10], s0[11]); \
  pr[14] = exp2_pair_fma(s0[28], s0[29], c0, kmant, kexpo); \
  pr[15] = exp2_pair_fma(s0[30], s0[31], c1, kmant, kexpo); \
  PIN_R(pr[8]); \
  PIN_R(pr[9]); \
  PIN_R(pr[10]); \
  PIN_R(pr[11]); \
  PIN_R(pr[12]); \
  PIN_R(pr[13]); \
  PIN_R(pr[14]); \
  PIN_R(pr[15]); \
  wg_fence(); \
  wg_rs_n24_t(o, pr + 8, dvt, 1); DESC_ADD(dvt, 16); \
  wg_rs_n24_t(o, pr + 12, dvt, 1); DESC_ADD(dvt, 16); \
  wg_commit(); \
} while (0)
#define PIN_S0 do { \
  PIN_F(s0[0]); \
  PIN_F(s0[1]); \
  PIN_F(s0[2]); \
  PIN_F(s0[3]); \
  PIN_F(s0[4]); \
  PIN_F(s0[5]); \
  PIN_F(s0[6]); \
  PIN_F(s0[7]); \
  PIN_F(s0[8]); \
  PIN_F(s0[9]); \
  PIN_F(s0[10]); \
  PIN_F(s0[11]); \
  PIN_F(s0[12]); \
  PIN_F(s0[13]); \
  PIN_F(s0[14]); \
  PIN_F(s0[15]); \
  PIN_F(s0[16]); \
  PIN_F(s0[17]); \
  PIN_F(s0[18]); \
  PIN_F(s0[19]); \
  PIN_F(s0[20]); \
  PIN_F(s0[21]); \
  PIN_F(s0[22]); \
  PIN_F(s0[23]); \
  PIN_F(s0[24]); \
  PIN_F(s0[25]); \
  PIN_F(s0[26]); \
  PIN_F(s0[27]); \
  PIN_F(s0[28]); \
  PIN_F(s0[29]); \
  PIN_F(s0[30]); \
  PIN_F(s0[31]); \
} while (0)
#define QK_S1 do { \
  wg_fence(); \
  wg_rs_n24(s1, qa, daug, 0); wg_rs_n24(s1, qf, dkt, 1); DESC_ADD(dkt, 48); \
  wg_rs_n40(s1 + 12, qf, dkt, 0); DESC_ADD(dkt, 80); \
  wg_commit(); \
} while (0)
#define EXP_PV_S1 do { \
  pr[0] = exp2_pair_mufu(s1[0], s1[1]); \
  pr[1] = exp2_pair_mufu(s1[2], s1[3]); \
  pr[2] = exp2_pair_fma(s1[12], s1[13], c0, kmant, kexpo); \
  pr[3] = exp2_pair_fma(s1[14], s1[15], c1, kmant, kexpo); \
  pr[4] = exp2_pair_fma(s1[16], s1[17], c0, kmant, kexpo); \
  pr[5] = exp2_pair_fma(s1[18], s1[19], c1, kmant, kexpo); \
  pr[6] = exp2_pair_mufu(s1[4], s1[5]); \
  pr[7] = exp2_pair_mufu(s1[6], s1[7]); \
  PIN_R(pr[0]); \
  PIN_R(pr[1]); \
  PIN_R(pr[2]); \
  PIN_R(pr[3]); \
  PIN_R(pr[4]); \
  PIN_R(pr[5]); \
  PIN_R(pr[6]); \
  PIN_R(pr[7]); \
  wg_fence(); \
  wg_rs_n24_t(o, pr + 0, dvt, 1); DESC_ADD(dvt, 16); \
  wg_rs_n24_t(o, pr + 4, dvt, 1); DESC_ADD(dvt, 16); \
  pr[8] = exp2_pair_fma(s1[20], s1[21], c0, kmant, kexpo); \
  pr[9] = exp2_pair_fma(s1[22], s1[23], c1, kmant, kexpo); \
  pr[10] = exp2_pair_fma(s1[24], s1[25], c0, kmant, kexpo); \
  pr[11] = exp2_pair_fma(s1[26], s1[27], c1, kmant, kexpo); \
  pr[12] = exp2_pair_mufu(s1[8], s1[9]); \
  pr[13] = exp2_pair_mufu(s1[10], s1[11]); \
  pr[14] = exp2_pair_fma(s1[28], s1[29], c0, kmant, kexpo); \
  pr[15] = exp2_pair_fma(s1[30], s1[31], c1, kmant, kexpo); \
  PIN_R(pr[8]); \
  PIN_R(pr[9]); \
  PIN_R(pr[10]); \
  PIN_R(pr[11]); \
  PIN_R(pr[12]); \
  PIN_R(pr[13]); \
  PIN_R(pr[14]); \
  PIN_R(pr[15]); \
  wg_fence(); \
  wg_rs_n24_t(o, pr + 8, dvt, 1); DESC_ADD(dvt, 16); \
  wg_rs_n24_t(o, pr + 12, dvt, 1); DESC_ADD(dvt, 16); \
  wg_commit(); \
} while (0)
#define PIN_S1 do { \
  PIN_F(s1[0]); \
  PIN_F(s1[1]); \
  PIN_F(s1[2]); \
  PIN_F(s1[3]); \
  PIN_F(s1[4]); \
  PIN_F(s1[5]); \
  PIN_F(s1[6]); \
  PIN_F(s1[7]); \
  PIN_F(s1[8]); \
  PIN_F(s1[9]); \
  PIN_F(s1[10]); \
  PIN_F(s1[11]); \
  PIN_F(s1[12]); \
  PIN_F(s1[13]); \
  PIN_F(s1[14]); \
  PIN_F(s1[15]); \
  PIN_F(s1[16]); \
  PIN_F(s1[17]); \
  PIN_F(s1[18]); \
  PIN_F(s1[19]); \
  PIN_F(s1[20]); \
  PIN_F(s1[21]); \
  PIN_F(s1[22]); \
  PIN_F(s1[23]); \
  PIN_F(s1[24]); \
  PIN_F(s1[25]); \
  PIN_F(s1[26]); \
  PIN_F(s1[27]); \
  PIN_F(s1[28]); \
  PIN_F(s1[29]); \
  PIN_F(s1[30]); \
  PIN_F(s1[31]); \
} while (0)
#define PIN_O do { \
  PIN_F(o[0]); \
  PIN_F(o[1]); \
  PIN_F(o[2]); \
  PIN_F(o[3]); \
  PIN_F(o[4]); \
  PIN_F(o[5]); \
  PIN_F(o[6]); \
  PIN_F(o[7]); \
  PIN_F(o[8]); \
  PIN_F(o[9]); \
  PIN_F(o[10]); \
  PIN_F(o[11]); \
} while (0)
#define PIN_ACC96 do { \
  PIN_F(acc[0]); \
  PIN_F(acc[1]); \
  PIN_F(acc[2]); \
  PIN_F(acc[3]); \
  PIN_F(acc[4]); \
  PIN_F(acc[5]); \
  PIN_F(acc[6]); \
  PIN_F(acc[7]); \
  PIN_F(acc[8]); \
  PIN_F(acc[9]); \
  PIN_F(acc[10]); \
  PIN_F(acc[11]); \
  PIN_F(acc[12]); \
  PIN_F(acc[13]); \
  PIN_F(acc[14]); \
  PIN_F(acc[15]); \
  PIN_F(acc[16]); \
  PIN_F(acc[17]); \
  PIN_F(acc[18]); \
  PIN_F(acc[19]); \
  PIN_F(acc[20]); \
  PIN_F(acc[21]); \
  PIN_F(acc[22]); \
  PIN_F(acc[23]); \
  PIN_F(acc[24]); \
  PIN_F(acc[25]); \
  PIN_F(acc[26]); \
  PIN_F(acc[27]); \
  PIN_F(acc[28]); \
  PIN_F(acc[29]); \
  PIN_F(acc[30]); \
  PIN_F(acc[31]); \
  PIN_F(acc[32]); \
  PIN_F(acc[33]); \
  PIN_F(acc[34]); \
  PIN_F(acc[35]); \
  PIN_F(acc[36]); \
  PIN_F(acc[37]); \
  PIN_F(acc[38]); \
  PIN_F(acc[39]); \
  PIN_F(acc[40]); \
  PIN_F(acc[41]); \
  PIN_F(acc[42]); \
  PIN_F(acc[43]); \
  PIN_F(acc[44]); \
  PIN_F(acc[45]); \
  PIN_F(acc[46]); \
  PIN_F(acc[47]); \
  PIN_F(acc[48]); \
  PIN_F(acc[49]); \
  PIN_F(acc[50]); \
  PIN_F(acc[51]); \
  PIN_F(acc[52]); \
  PIN_F(acc[53]); \
  PIN_F(acc[54]); \
  PIN_F(acc[55]); \
  PIN_F(acc[56]); \
  PIN_F(acc[57]); \
  PIN_F(acc[58]); \
  PIN_F(acc[59]); \
  PIN_F(acc[60]); \
  PIN_F(acc[61]); \
  PIN_F(acc[62]); \
  PIN_F(acc[63]); \
  PIN_F(acc[64]); \
  PIN_F(acc[65]); \
  PIN_F(acc[66]); \
  PIN_F(acc[67]); \
  PIN_F(acc[68]); \
  PIN_F(acc[69]); \
  PIN_F(acc[70]); \
  PIN_F(acc[71]); \
  PIN_F(acc[72]); \
  PIN_F(acc[73]); \
  PIN_F(acc[74]); \
  PIN_F(acc[75]); \
  PIN_F(acc[76]); \
  PIN_F(acc[77]); \
  PIN_F(acc[78]); \
  PIN_F(acc[79]); \
  PIN_F(acc[80]); \
  PIN_F(acc[81]); \
  PIN_F(acc[82]); \
  PIN_F(acc[83]); \
  PIN_F(acc[84]); \
  PIN_F(acc[85]); \
  PIN_F(acc[86]); \
  PIN_F(acc[87]); \
  PIN_F(acc[88]); \
  PIN_F(acc[89]); \
  PIN_F(acc[90]); \
  PIN_F(acc[91]); \
  PIN_F(acc[92]); \
  PIN_F(acc[93]); \
  PIN_F(acc[94]); \
  PIN_F(acc[95]); \
} while (0)
#define PIN_R16 do { \
  PIN_F(r[0]); \
  PIN_F(r[1]); \
  PIN_F(r[2]); \
  PIN_F(r[3]); \
  PIN_F(r[4]); \
  PIN_F(r[5]); \
  PIN_F(r[6]); \
  PIN_F(r[7]); \
  PIN_F(r[8]); \
  PIN_F(r[9]); \
  PIN_F(r[10]); \
  PIN_F(r[11]); \
  PIN_F(r[12]); \
  PIN_F(r[13]); \
  PIN_F(r[14]); \
  PIN_F(r[15]); \
  PIN_F(ro[0]); \
  PIN_F(ro[1]); \
  PIN_F(ro[2]); \
  PIN_F(ro[3]); \
  PIN_F(ro[4]); \
  PIN_F(ro[5]); \
  PIN_F(ro[6]); \
  PIN_F(ro[7]); \
  PIN_F(ro[8]); \
  PIN_F(ro[9]); \
  PIN_F(ro[10]); \
  PIN_F(ro[11]); \
  PIN_F(ro[12]); \
  PIN_F(ro[13]); \
  PIN_F(ro[14]); \
  PIN_F(ro[15]); \
} while (0)
#define PIN_QA do { \
  PIN_R(qa[0]); \
  PIN_R(qa[1]); \
  PIN_R(qa[2]); \
  PIN_R(qa[3]); \
  PIN_R(qf[0]); \
  PIN_R(qf[1]); \
  PIN_R(qf[2]); \
  PIN_R(qf[3]); \
} while (0)

__device__ __forceinline__ float3 ln_stats(const uint4& xa, const uint4& xb, const uint4& wa, const uint4& wb) {
  const uint32_t xw[8] = {xa.x, xa.y, xa.z, xa.w, xb.x, xb.y, xb.z, xb.w};
  const uint32_t ww[8] = {wa.x, wa.y, wa.z, wa.w, wb.x, wb.y, wb.z, wb.w};
  float s0 = 0.f, s1 = 0.f, d0 = 0.f, d1 = 0.f, w0 = 0.f, w1 = 0.f;
#pragma unroll
  for (int i = 0; i < 8; i++) {
    s0 += bf_lo(xw[i]); s1 += bf_hi(xw[i]);
    d0 = fmaf(bf_lo(xw[i]), bf_lo(ww[i]), d0); d1 = fmaf(bf_hi(xw[i]), bf_hi(ww[i]), d1);
    w0 += bf_lo(ww[i]); w1 += bf_hi(ww[i]);
  }
  float mean = (s0 + s1) * (1.0f / 16.0f), dot = d0 + d1, ws = w0 + w1, q0 = 0.f, q1 = 0.f;
#pragma unroll
  for (int i = 0; i < 8; i++) {
    const float a = bf_lo(xw[i]) - mean, c = bf_hi(xw[i]) - mean;
    q0 = fmaf(a, a, q0); q1 = fmaf(c, c, q1);
  }
  float m2 = q0 + q1;
#pragma unroll
  for (int o = 1; o < 32; o <<= 1) {
    const float mo = __shfl_xor_sync(0xffffffffu, mean, o), qo = __shfl_xor_sync(0xffffffffu, m2, o);
    dot += __shfl_xor_sync(0xffffffffu, dot, o);
    ws += __shfl_xor_sync(0xffffffffu, ws, o);
    const float dl = mo - mean;
    m2 = fmaf(dl * dl, 8.0f * o, m2 + qo);
    mean = 0.5f * (mean + mo);
  }
  const float mb = bf16r(mean);
  const float rs = 1.0f / bf16r(sqrtf(bf16r(bf16r(m2 * (1.0f / 512.0f)) + 1e-5f)));
  return make_float3(mb, rs, (dot - mb * ws) * rs);
}
__device__ __forceinline__ uint32_t ln_apply(uint32_t v, float mb, float rs) {
  const uint32_t d = pack_bf16(bf_lo(v) - mb, bf_hi(v) - mb);
  return pack_bf16(bf_lo(d) * rs, bf_hi(d) * rs);
}

__device__ __noinline__ void attn_fallback(uint32_t q0, uint32_t q1, uint32_t q2, uint32_t q3, const uint8_t* kvh,
                                           uint32_t* odst, uint32_t* qscr) {
  const int lane = threadIdx.x & 31, g = lane >> 2, t = lane & 3;
  qscr[g * 8 + t] = q0;
  qscr[(g + 8) * 8 + t] = q1;
  qscr[g * 8 + 4 + t] = q2;
  qscr[(g + 8) * 8 + 4 + t] = q3;
  __threadfence();
  __syncwarp();
  const int row = lane >> 1, par = lane & 1;
  float q[16], o[16];
#pragma unroll
  for (int i = 0; i < 8; i++) { uint32_t v = __ldcg(qscr + row * 8 + i); q[2 * i] = bf_lo(v); q[2 * i + 1] = bf_hi(v); }
#pragma unroll
  for (int i = 0; i < 16; i++) o[i] = 0.f;
  float m = -INFINITY, l = 0.f;
#pragma unroll 1
  for (int key = par * 1024; key < par * 1024 + 1024; key++) {
    const int blk = key >> 7, kk = key & 127, G = kk >> 3;
    const uint8_t* kp = kvh + blk * 8192 + (G >> 3) * 2048 + ((KPERM >> (4 * (G & 7))) & 7) * 256 + (kk & 7) * 16;
    const uint8_t* vp = kvh + blk * 8192 + 4096 + kk * 16;
    const uint4 k0 = __ldcg((const uint4*)kp), k1 = __ldcg((const uint4*)(kp + 128));
    const uint4 v0 = __ldcg((const uint4*)vp), v1 = __ldcg((const uint4*)(vp + 2048));
    const uint32_t kw[8] = {k0.x, k0.y, k0.z, k0.w, k1.x, k1.y, k1.z, k1.w};
    const uint32_t vw[8] = {v0.x, v0.y, v0.z, v0.w, v1.x, v1.y, v1.z, v1.w};
    float s = 0.f;
#pragma unroll
    for (int i = 0; i < 8; i++) { s = fmaf(q[2 * i], bf_lo(kw[i]), s); s = fmaf(q[2 * i + 1], bf_hi(kw[i]), s); }
    if (s == -INFINITY) continue;
    const float mn = fmaxf(m, s), a = exp2f(m - mn), p = exp2f(s - mn);
    m = mn;
    l = l * a + p;
#pragma unroll
    for (int i = 0; i < 8; i++) { o[2 * i] = o[2 * i] * a + p * bf_lo(vw[i]); o[2 * i + 1] = o[2 * i + 1] * a + p * bf_hi(vw[i]); }
  }
  const float m2 = __shfl_xor_sync(0xffffffffu, m, 1), l2 = __shfl_xor_sync(0xffffffffu, l, 1);
  const float mn = fmaxf(m, m2);
  const float a = (m == -INFINITY) ? 0.f : exp2f(m - mn), a2 = (m2 == -INFINITY) ? 0.f : exp2f(m2 - mn);
  const float inv = 1.0f / (l * a + l2 * a2);
#pragma unroll
  for (int i = 0; i < 16; i++) { const float other = __shfl_xor_sync(0xffffffffu, o[i], 1); o[i] = (o[i] * a + other * a2) * inv; }
#pragma unroll
  for (int i = 0; i < 4; i++)
    odst[((row & 7) * 4 + i) * 4 + par * 2 + (row >> 3)] =
        nonzero(par ? pack_bf16(o[8 + 2 * i], o[9 + 2 * i]) : pack_bf16(o[2 * i], o[2 * i + 1]));
}

__device__ __forceinline__ void fma8(float* a, float v, const uint4& w) {
  a[0] = fmaf(v, bf_lo(w.x), a[0]); a[1] = fmaf(v, bf_hi(w.x), a[1]); a[2] = fmaf(v, bf_lo(w.y), a[2]); a[3] = fmaf(v, bf_hi(w.y), a[3]);
  a[4] = fmaf(v, bf_lo(w.z), a[4]); a[5] = fmaf(v, bf_hi(w.z), a[5]); a[6] = fmaf(v, bf_lo(w.w), a[6]); a[7] = fmaf(v, bf_hi(w.w), a[7]);
}

__device__ __forceinline__ void cp16(uint32_t dst, const void* src, bool on) {
  asm volatile("{\n.reg .pred p;\nsetp.ne.u32 p, %2, 0;\n@p cp.async.cg.shared.global [%0], [%1], 16;\n}" :: "r"(dst), "l"(src), "r"((uint32_t)on) : "memory");
}
__device__ __forceinline__ void ffn_cta(int j, uint8_t* sm, const __nv_bfloat16* x, const __nv_bfloat16* wgate,
                                        const __nv_bfloat16* wup, const __nv_bfloat16* wdown) {
  const int tid = threadIdx.x, lane = tid & 31;
  float* xs = (float*)(sm + 196608);
  float* hs = xs + 512;
  float* red = xs + 1024;
  unsigned* ms = (unsigned*)(red + 4096);
  const uint32_t win = (uint32_t)__cvta_generic_to_shared(sm) + tid * 16;
  if (tid == 0) { const unsigned e = __ldcg(&g_epoch[(128 + j) * 8]) + 1u; ms[16] = e; g_epoch[(128 + j) * 8] = e; }
  __syncthreads();
  const unsigned e1 = ms[16];
  const int t4 = min(tid, 447), kg = t4 / 112, r = t4 % 112, mat = r / 56, cg = r % 56;
  const uint4* p1 = (const uint4*)((mat ? wup : wgate) + (size_t)kg * 128 * 1792 + 448 * j + cg * 8);
  const int cg2 = tid & 63, kg2 = tid >> 6;
  const uint4* p2 = (const uint4*)(wdown + (size_t)(448 * j + kg2 * 56) * 512 + cg2 * 8);
#define FFN_ISSUE(G) do { \
    _Pragma("unroll") for (int u = 0; u < 4; u++) { \
      const int k = (G) * 4 + u; \
      cp16(win + (k % 24) * 8192, k < 128 ? p1 + (size_t)k * 224 : p2 + (size_t)(k - 128) * 64, k < 128 ? tid < 448 : k < 184); \
    } \
    asm volatile("cp.async.commit_group;" ::: "memory"); } while (0)
  for (int gi = 0; gi < 6; gi++) FFN_ISSUE(gi);
  for (const long long t0 = clock64(); clock64() - t0 < 5000;) __nanosleep(100);
  unsigned key = 0u;
#pragma unroll
  for (int i = 0; i < 4; i++) {
    uint4 v = ld_rec(&g_rec[tid + 512 * i]);
    wait_rec(v, &g_rec[tid + 512 * i], e1);
    key = max(key, v.z);
  }
  key = __reduce_max_sync(0xffffffffu, key);
  if (lane == 0) ms[tid >> 5] = key;
  __syncthreads();
  key = __reduce_max_sync(0xffffffffu, ms[lane & 15]);
  if (tid < 64) {
    const int idx = 2047 - (int)(key & 0xFFFFu);
    const uint4 st = ld_rec(&g_rec[idx]);
    const uint4 v = __ldg((const uint4*)(x + (size_t)idx * 512 + tid * 8));
    const uint32_t w[4] = {v.x, v.y, v.z, v.w};
#pragma unroll
    for (int i = 0; i < 4; i++) {
      const uint32_t n = ln_apply(w[i], __uint_as_float(st.x), __uint_as_float(st.y));
      xs[tid * 8 + 2 * i] = bf_lo(n); xs[tid * 8 + 2 * i + 1] = bf_hi(n);
    }
  }
  if (tid == 64 && j == 0) st_tag64(&g_sel, key, e1);
  __syncthreads();
  TM(1);
  float a[8] = {0.f, 0.f, 0.f, 0.f, 0.f, 0.f, 0.f, 0.f};
#pragma unroll 1
  for (int gi = 0; gi < 32; gi++) {
    asm volatile("cp.async.wait_group 5;" ::: "memory");
#pragma unroll
    for (int u = 0; u < 4; u++) fma8(a, xs[kg * 128 + gi * 4 + u], lds128(win + ((gi * 4 + u) % 24) * 8192));
    FFN_ISSUE(gi + 6);
  }
  if (tid < 448) {
#pragma unroll
    for (int i = 0; i < 8; i++) red[(kg * 2 + mat) * 448 + cg * 8 + i] = a[i];
  }
  __syncthreads();
  TM(2);
  if (tid < 448) {
    const float gv = bf16r(red[tid] + red[896 + tid] + red[1792 + tid] + red[2688 + tid]);
    const float uv = bf16r(red[448 + tid] + red[1344 + tid] + red[2240 + tid] + red[3136 + tid]);
    const float sg = bf16r(gv / (1.0f + expf(-gv)));
    hs[tid] = bf16r(sg * uv);
  }
  __syncthreads();
#pragma unroll
  for (int i = 0; i < 8; i++) a[i] = 0.f;
#pragma unroll 1
  for (int gi = 32; gi < 46; gi++) {
    asm volatile("cp.async.wait_group 5;" ::: "memory");
#pragma unroll
    for (int u = 0; u < 4; u++) fma8(a, hs[kg2 * 56 + (gi - 32) * 4 + u], lds128(win + ((gi * 4 + u) % 24) * 8192));
    FFN_ISSUE(gi + 6);
  }
#pragma unroll
  for (int i = 0; i < 8; i++) red[kg2 * 512 + cg2 * 8 + i] = a[i];
  __syncthreads();
  float y = 0.f;
#pragma unroll
  for (int k = 0; k < 8; k++) y += red[k * 512 + tid];
  st_tag64(&g_y[j * 512 + tid], __float_as_uint(y), e1);
}

__device__ __forceinline__ void make_qa(uint32_t* qa, float m0, float m1, int t) {
  const float h0 = bf16r(m0), h1 = bf16r(m1);
  const uint32_t p0 = pack_bf16(h0, m0 - h0), p1 = pack_bf16(h1, m1 - h1);
  const uint32_t dl = (t == 1) ? 0xBAF03F18u : 0u;
  qa[0] = (t == 0) ? p0 : dl;
  qa[1] = (t == 0) ? p1 : dl;
}
__device__ __forceinline__ void make_c(float& c0, float& c1, float m0, float m1) {
  asm("mul.rn.f32 %0, %1, 0f00000080;" : "=f"(c0) : "f"(m0 + 127.f));
  asm("mul.rn.f32 %0, %1, 0f00000080;" : "=f"(c1) : "f"(m1 + 127.f));
  c0 = (fabsf(m0) + fabsf(m1) < 30000.f) ? c0 : __uint_as_float(0x7FC00000u);
}
__device__ __forceinline__ void row_offsets(const float* s, float& m0, float& m1) {
  float a0 = fmaxf(s[0], s[1]), a1 = fmaxf(s[2], s[3]), b0 = fmaxf(s[4], s[5]), b1 = fmaxf(s[6], s[7]);
#pragma unroll
  for (int j = 2; j < 8; j += 2) {
    a0 = fmaxf(a0, fmaxf(s[4 * j], s[4 * j + 1])); a1 = fmaxf(a1, fmaxf(s[4 * j + 2], s[4 * j + 3]));
    b0 = fmaxf(b0, fmaxf(s[4 * j + 4], s[4 * j + 5])); b1 = fmaxf(b1, fmaxf(s[4 * j + 6], s[4 * j + 7]));
  }
  a0 = fmaxf(a0, b0); a1 = fmaxf(a1, b1);
  a0 = fmaxf(a0, __shfl_xor_sync(0xffffffffu, a0, 1)); a1 = fmaxf(a1, __shfl_xor_sync(0xffffffffu, a1, 1));
  a0 = fmaxf(a0, __shfl_xor_sync(0xffffffffu, a0, 2)); a1 = fmaxf(a1, __shfl_xor_sync(0xffffffffu, a1, 2));
  m0 = -(ceilf(a0) + M_MARGIN);
  m1 = -(ceilf(a1) + M_MARGIN);
}
__device__ __forceinline__ void publish_o(const float* o, uint4* odst, const uint8_t* kvh, uint32_t qaddr, uint32_t* qscr) {
  const int lane = threadIdx.x & 31;
  const float l0 = __shfl_sync(0xffffffffu, o[8], lane & 28), l1 = __shfl_sync(0xffffffffu, o[10], lane & 28);
  float r0, r1;
  asm("rcp.approx.ftz.f32 %0, %1;" : "=f"(r0) : "f"(l0));
  asm("rcp.approx.ftz.f32 %0, %1;" : "=f"(r1) : "f"(l1));
  const float c0 = fmaf(o[0], 0.f, o[1] * 0.f) + fmaf(o[2], 0.f, o[3] * 0.f), c1 = fmaf(o[4], 0.f, o[5] * 0.f) + fmaf(o[6], 0.f, o[7] * 0.f);
  const bool ok = (l0 + l1) + (c0 + c1) < 1e36f;
  if (__all_sync(0xffffffffu, ok)) {
    odst[lane] = make_uint4(nonzero(pack_bf16(o[0] * r0, o[1] * r0)), nonzero(pack_bf16(o[2] * r1, o[3] * r1)),
                            nonzero(pack_bf16(o[4] * r0, o[5] * r0)), nonzero(pack_bf16(o[6] * r1, o[7] * r1)));
  } else {
    const uint4 q = lds128(qaddr);
    attn_fallback(q.x, q.y, q.z, q.w, kvh, (uint32_t*)odst, qscr);
  }
  __syncwarp();
}

__global__ void __cluster_dims__(2, 1, 1) __launch_bounds__(512, 1)
fused_kernel(const __grid_constant__ CUtensorMap tm_x, const __grid_constant__ CUtensorMap tm_wqkv,
             const __grid_constant__ CUtensorMap tm_wo, const __nv_bfloat16* __restrict__ x,
             const __nv_bfloat16* __restrict__ wqkv, const __nv_bfloat16* __restrict__ wr,
             const __nv_bfloat16* __restrict__ wgate, const __nv_bfloat16* __restrict__ wup,
             const __nv_bfloat16* __restrict__ wdown, __nv_bfloat16* __restrict__ out) {
  extern __shared__ __align__(1024) uint8_t smem[];
  const int b = blockIdx.x;
  TM(0); TMG(30);
  if (b >= 128) { ffn_cta(b - 128, smem, x, wgate, wup, wdown); TM(12); TMG(31); return; }
  const int tid = threadIdx.x, lane = tid & 31;
  const int warp = (int)__reduce_max_sync(0xffffffffu, (unsigned)tid >> 5);
  const int wgi = warp >> 2, wq = warp & 3, hf = wgi & 1, s = wgi >> 1;
  const int g = lane >> 2, t = lane & 3;
  const int rb = b & 15, cb = b >> 4;
  const uint32_t sb = (uint32_t)__cvta_generic_to_shared(smem);
  const uint32_t bar = sb + SM_BAR;
  volatile unsigned* misc = (volatile unsigned*)(smem + SM_MISC);

  const uint32_t ring = sb + s * R_STREAM;
  const uint32_t stash = sb + SM_STASH + tid * 16;
  if (s == 1) {
    const int hw = warp - 8, ht = tid - 256;
    const unsigned ticket = ld_relaxed(&g_epoch[b * 8]) + 1u;
    bar_sync(3, 512);
    const int row = rb * 128 + cb * 16 + hw * 2;
    const uint4* xp = (const uint4*)(x + (size_t)row * 512) + lane;
    const uint4 xa = ld_nc128(xp), xb = ld_nc128(xp + 32), xc = ld_nc128(xp + 64), xd = ld_nc128(xp + 96);
    const uint4 wa = ld_nc128((const uint4*)wr + lane), wb = ld_nc128((const uint4*)wr + 32 + lane);
    const int l24 = min(lane, 23);
    const uint4* wp = (const uint4*)(wqkv + (size_t)(rb * 32 + hw * 4) * 1536 + (l24 >> 3) * 512 + cb * 64 + (l24 & 7) * 8);
    const uint4 c0 = ld_nc128(wp), c1 = ld_nc128(wp + 192), c2 = ld_nc128(wp + 384), c3 = ld_nc128(wp + 576);
    TM(26);
    if (ht >= 64 && ht < 64 + 48) {
      const int i = ht - 64;
      const uint32_t one = ((i >> 3) & 1) ? 0u : 0x3F803F80u;
      sts128(sb + SM_AUG + i * 16, one, one, 0u, 0u);
    }
    if (ht == 128) sts128(sb + SM_MISC + 80, 0x3F003F00u, 0x00010001u, 0u, 0u);
    if (lane == 0) {
#pragma unroll
      for (int i = 0; i < 10; i++) mbar_init(sb + SM_RBAR + 80 * hw + 8 * i, (hw & 2) ? 2 : 1);
      asm volatile("fence.mbarrier_init.release.cluster;" ::: "memory");
    }
    __syncwarp();
    const float3 sa = ln_stats(xa, xb, wa, wb), sc = ln_stats(xc, xd, wa, wb);
    if (lane < 24) {
      const uint32_t a = sb + SM_RED + hw * 768 + lane * 32;
      sts128(a, __float_as_uint((bf_lo(c0.x) + bf_lo(c1.x)) + (bf_lo(c2.x) + bf_lo(c3.x))), __float_as_uint((bf_hi(c0.x) + bf_hi(c1.x)) + (bf_hi(c2.x) + bf_hi(c3.x))),
                __float_as_uint((bf_lo(c0.y) + bf_lo(c1.y)) + (bf_lo(c2.y) + bf_lo(c3.y))), __float_as_uint((bf_hi(c0.y) + bf_hi(c1.y)) + (bf_hi(c2.y) + bf_hi(c3.y))));
      sts128(a + 16, __float_as_uint((bf_lo(c0.z) + bf_lo(c1.z)) + (bf_lo(c2.z) + bf_lo(c3.z))), __float_as_uint((bf_hi(c0.z) + bf_hi(c1.z)) + (bf_hi(c2.z) + bf_hi(c3.z))),
                     __float_as_uint((bf_lo(c0.w) + bf_lo(c1.w)) + (bf_lo(c2.w) + bf_lo(c3.w))), __float_as_uint((bf_hi(c0.w) + bf_hi(c1.w)) + (bf_hi(c2.w) + bf_hi(c3.w))));
    }
    if (lane < 2) {
      const float3 v = lane ? sc : sa;
      uint32_t rbits = pack_bf16(v.z + 0.0f, 0.f) & 0xFFFFu;
      rbits = (rbits & 0x8000u) ? (~rbits & 0xFFFFu) : (rbits | 0x8000u);
      if (v.z != v.z) rbits = 0u;
      sts128(sb + SM_RED + 6144 + (hw * 2 + lane) * 16, __float_as_uint(v.x), __float_as_uint(v.y), (rbits << 16) | (uint32_t)(2047 - row - lane), 0u);
    }
    if (ht == 0) misc[16] = ticket;
    TM(1);
    bar_sync(6, 256);
    const unsigned e = misc[16];
    if (ht == 0) g_epoch[b * 8] = ticket;
    if (hw < 6) {
      const float* rp = (const float*)(smem + SM_RED) + ht;
      float v = 0.f;
#pragma unroll
      for (int i = 0; i < 8; i++) v += rp[i * 192];
      st_tag64(&g_cs[(cb * 16 + rb) * 192 + ht], __float_as_uint(v), e);
    } else if (ht < 208) {
      const uint4 v = lds128(sb + SM_RED + 6144 + (ht - 192) * 16);
      st_rec(&g_rec[rb * 128 + cb * 16 + ht - 192], v.x, v.y, v.z, e);
    }
    __syncwarp();
    TM(2);
    mbar_wait(bar + B_FULLA + 8 * GATHER_AT, 0);
    if (hw < 6) {
      uint32_t gs[32];
      ld_cs(gs, &g_cs[cb * 3072 + ht]);
      wait_cs(gs, &g_cs[cb * 3072 + ht], e);
      float v = 0.f;
#pragma unroll
      for (int i = 0; i < 16; i += 2) v += __uint_as_float(gs[2 * i]) + __uint_as_float(gs[2 * i + 2]);
      const float hi = bf16r(v);
      sts128(sb + SM_RED + 8192 + ht * 16, pack_bf16(hi, v - hi), 0u, 0u, 0u);
    } else {
      const uint4* rp = &g_rec[rb * 128 + ht - 192];
      uint4 r0 = ld_rec(rp), r1 = ld_rec(rp + 64);
      wait_rec(r0, rp, e);
      wait_rec(r1, rp + 64, e);
      ((float2*)(smem + SM_STAT))[ht - 192] = make_float2(__uint_as_float(r0.x), __uint_as_float(r0.y));
      ((float2*)(smem + SM_STAT))[ht - 128] = make_float2(__uint_as_float(r1.x), __uint_as_float(r1.y));
    }
    TM(3);
    fence_async_smem();
    bar_arrive(2, 512);
    bar_sync(1, 512);
    if (warp == 15) {
      elect_tma2d(sb + SM_WO, &tm_wo, 64 * (b & 7), 0, bar + B_WO, 65536);
      elect_tma2d(sb + SM_WO + 32768, &tm_wo, 64 * (b & 7), 256, bar + B_WO, 0);
    }
#pragma unroll
    for (int i = 0; i < 6; i++) sts128(sb + ((ht >> 7) + 2 * i) * R_SLOT + 8192 + (ht & 127) * 16, 0x00003F80u, 0u, 0u, 0u);
  } else {
    if (warp == 0) {
      if (lane == 0) {
#pragma unroll
        for (int i = 0; i < 9; i++) mbar_init(bar + 8 * i, (i >= 5 && i < 8) ? 2 : 1);
        asm volatile("fence.mbarrier_init.release.cluster;" ::: "memory");
      }
      __syncwarp();
      elect_load_ax(sb, &tm_wqkv, &tm_x, 0, 64 * cb, rb * 128, bar + B_FULLA);
    }
    TM(26);
    bar_sync(3, 512);
    if (warp == 0) {
#pragma unroll
      for (int j = 1; j < AWIN; j++) elect_load_ax(sb + j * A_STAGE, &tm_wqkv, &tm_x, 64 * j, 64 * cb, rb * 128, bar + B_FULLA + 8 * j);
    }
    float acc[96];
#pragma unroll
    for (int i = 0; i < 96; i++) acc[i] = 0.f;
#pragma unroll
    for (int j = 0; j < 8; j++) {
      const int sl = j % 5;
      mbar_wait(bar + B_FULLA + 8 * sl, j / 5);
      TM(13 + j);
      uint64_t da = mkdesc(sb + sl * A_STAGE + hf * 8192, 16, 1024, 1);
      uint64_t db = mkdesc(sb + sl * A_STAGE + A_WOFF, 8192, 1024, 1);
      wg_fence();
#pragma unroll
      for (int kk = 0; kk < 4; kk++) { wg_ss_n192_t(acc, da, db, 1); DESC_ADD(da, 2); DESC_ADD(db, 128); }
      wg_commit();
      if (AWIN < 5 && j + AWIN < 8 && warp == 4 * (j & 1)) {
        if (j + AWIN >= 5) mbar_wait(bar + B_EMPTYA + 8 * (j + AWIN - 5), 0);
        elect_load_ax(sb + ((j + AWIN) % 5) * A_STAGE, &tm_wqkv, &tm_x, 64 * (j + AWIN), 64 * cb, rb * 128, bar + B_FULLA + 8 * ((j + AWIN) % 5));
      }
      if (j >= 1 && j <= 3) {
        wg_wait<1>();
        arrive_if(bar + B_EMPTYA + 8 * (j - 1), (tid & 127) == 0);
        if (AWIN == 5 && warp == 4) {
          mbar_wait(bar + B_EMPTYA + 8 * (j - 1), 0);
          elect_load_ax(sb + (j - 1) * A_STAGE, &tm_wqkv, &tm_x, 64 * (j + 4), 64 * cb, rb * 128, bar + B_FULLA + 8 * (j - 1));
        }
      }
    }
    bar_sync(2, 512);
    const float2 st0 = ((const float2*)(smem + SM_STAT))[hf * 64 + wq * 16 + g];
    const float2 st1 = ((const float2*)(smem + SM_STAT))[hf * 64 + wq * 16 + g + 8];
    {
      uint32_t am[4] = {t ? 0u : pack_bf16(-st0.x, -st0.x), t ? 0u : pack_bf16(-st1.x, -st1.x), 0u, 0u};
      PIN_R(am[0]); PIN_R(am[1]); PIN_R(am[2]); PIN_R(am[3]);
      wg_fence();
      wg_rs_n192(acc, am, mkdesc(sb + SM_RED + 8192, 0, 128, 0), 1);
      wg_commit();
    }
    wg_wait<0>();
    PIN_ACC96;
    TM(4);
    bar_sync(1, 512);
    const int mi = lane >> 3, i8 = 2 * wq + (mi & 1);
    const uint32_t ko = sb + hf * 2048 + ((KPERM >> (4 * i8)) & 7) * 256 + (mi >> 1) * 128 + (lane & 7) * 16;
    const uint32_t vo = sb + 4096 + (mi >> 1) * 2048 + (hf * 8 + i8) * 128 + (lane & 7) * 16;
#pragma unroll
    for (int sec = 2; sec >= 0; sec--) {
      const float k = sec ? 1.0f : 0.25f * 1.4426950408889634f;
      const float r0 = st0.y * k, r1 = st1.y * k;
#pragma unroll
      for (int h = 0; h < 4; h++) {
        uint32_t f[4];
#pragma unroll
        for (int d = 0; d < 2; d++) {
          const int j = sec * 8 + h * 2 + d;
          f[2 * d] = pack_bf16(acc[4 * j] * r0, acc[4 * j + 1] * r0);
          f[2 * d + 1] = pack_bf16(acc[4 * j + 2] * r1, acc[4 * j + 3] * r1);
        }
        const uint32_t so = (h >> 1) * R_STREAM + (3 + ((h & 1) ^ 1)) * R_SLOT;
        if (sec == 0) sts128(stash + (h >> 1) * 4096 + ((h & 1) ^ 1) * 16384, f[0], f[1], f[2], f[3]);
        else stsm4((sec == 1 ? ko : vo) + so, f[0], f[1], f[2], f[3]);
      }
    }
  }
  fence_async_smem();
  bar_sync(1, 512);
  const unsigned e1 = __reduce_max_sync(0xffffffffu, misc[16]);
  TM(5);

  const uint32_t bfull = sb + SM_RBAR + 320 * s;
  const uint64_t daug = mkdesc(sb + SM_AUG, 128, 256, 0);
  const uint64_t dk0 = mkdesc(ring, 128, 256, 0);
  const uint64_t dv0 = mkdesc(ring + 4096, 128, 2048, 0);
  const bool loader = (hf == 1) && (wq == 0);
  const uint8_t* kvs = g_kv + (cb * 4 + s * 2) * 131072;
  const uint32_t is_t0 = (tid & 127) == 0;
  if (loader)
    asm volatile("{\n.reg .pred p;\nelect.sync _|p, 0xffffffff;\n"
                 "@p cp.async.bulk.global.shared::cta.bulk_group [%0], [%1], 8192;\n"
                 "@p cp.async.bulk.global.shared::cta.bulk_group [%2], [%3], 8192;\n"
                 "@p cp.async.bulk.commit_group;\n}"
                 :: "l"(kvs + rb * 8192), "r"(ring + 4 * R_SLOT), "l"(kvs + 131072 + rb * 8192), "r"(ring + 3 * R_SLOT) : "memory");
  const uint4 kc = lds128(sb + SM_MISC + 80);
  const uint32_t kmant = kc.x, kexpo = kc.y;
  const uint4* const osrc = g_o + ((b >> 3) * 32 + s * 2) * 256;
  uint4* const obase = g_o + (rb * 32 + cb * 4 + s * 2) * 256 + hf * 128 + wq * 32;
  uint32_t* const qscr = g_qscr + (b * 16 + warp) * 128;
  {
    float s0[32], s1[32], o[12];
    uint32_t pr[16], qa[4], qf[4], qo[4];
    float c0, c1;
    {
      const uint4 v = lds128(stash), w = lds128(stash + 16384);
      qf[0] = v.x; qf[1] = v.y; qf[2] = v.z; qf[3] = v.w;
      qo[0] = w.x; qo[1] = w.y; qo[2] = w.z; qo[3] = w.w;
    }
#pragma unroll
    for (int i = 0; i < 32; i++) { s0[i] = 0.f; s1[i] = 0.f; }
#pragma unroll
    for (int i = 0; i < 12; i++) o[i] = 0.f;
    uint64_t dkt = dk0 + 3 * (R_SLOT / 16), dvt = dv0 + 3 * (R_SLOT / 16);
    PIN_S0; PIN_S1; PIN_O;
    wg_fence();
    wg_rs_n24(s0, qf, dkt, 0);
    wg_rs_n40(s0 + 12, qf, dkt + 48, 0);
    wg_rs_n24(s1, qo, dkt + R_SLOT / 16, 0);
    wg_rs_n40(s1 + 12, qo, dkt + R_SLOT / 16 + 48, 0);
    DESC_ADD(dkt, 128);
    wg_commit();
    wg_wait<0>();
    PIN_S0; PIN_S1;
    {
      float m0, m1, n0, n1;
      row_offsets(s0, m0, m1);
      row_offsets(s1, n0, n1);
      sts128(stash + 8192, __float_as_uint(m0), __float_as_uint(m1), __float_as_uint(n0), __float_as_uint(n1));
      make_qa(qa, m0, m1, t);
      qa[2] = kc.z; qa[3] = kc.w;
      make_c(c0, c1, m0, m1);
#pragma unroll
      for (int j = 0; j < NMUFU / 8; j++) {
        s0[4 * j] += m0 + LOG2C; s0[4 * j + 1] += m0 + LOG2C;
        s0[4 * j + 2] += m1 + LOG2C; s0[4 * j + 3] += m1 + LOG2C;
      }
    }
    if (loader) {
      asm volatile("{\n.reg .pred p;\nelect.sync _|p, 0xffffffff;\n@p cp.async.bulk.wait_group 0;\n}" ::: "memory");
      __syncwarp();
      if (lane < 2) st_rec(&g_flag[b * 4 + s * 2 + lane], e1 - 1u, e1, 0u, 0u);
      __syncwarp();
    }
    TM(21);
#pragma unroll 1
    for (int loc = 0; loc < 2; loc++) {
      PIN_S0; PIN_O;
      QK_S1;
      EXP_PV_S0;
      if (loc) mbar_wait(bfull, 0);
      wg_wait<0>();
      PIN_S1; PIN_O;
      dkt = dk0;
      QK_S0;
      EXP_PV_S1;
      wg_wait<0>();
      PIN_S0; PIN_O;
      if (loc) break;
      const uint4 q = lds128(stash + 16384), m = lds128(stash + 8192);
      qf[0] = q.x; qf[1] = q.y; qf[2] = q.z; qf[3] = q.w;
      make_qa(qa, __uint_as_float(m.z), __uint_as_float(m.w), t);
      PIN_QA;
      dkt = dk0 + 4 * (R_SLOT / 16);
      dvt = dv0 + 4 * (R_SLOT / 16);
      QK_S0;
      if (loader) {
        wait_flag_warp(&g_flag[(cb * 16 + (lane & 15)) * 4 + s * 2].y, e1);
        elect_load3(ring, kvs + ((rb + 1) & 15) * 8192, kvs + ((rb + 2) & 15) * 8192, kvs + ((rb + 3) & 15) * 8192, bfull);
      }
      make_c(c0, c1, __uint_as_float(m.z), __uint_as_float(m.w));
      obase[lane] = make_uint4(0u, 0u, 0u, 0u);
      obase[256 + lane] = make_uint4(0u, 0u, 0u, 0u);
      sts128(stash + 8192, m.x, m.y, __float_as_uint(o[8]), __float_as_uint(o[10]));
      sts128(stash + 24576, __float_as_uint(o[0]), __float_as_uint(o[1]), __float_as_uint(o[2]), __float_as_uint(o[3]));
      sts128(stash + 32768, __float_as_uint(o[4]), __float_as_uint(o[5]), __float_as_uint(o[6]), __float_as_uint(o[7]));
#pragma unroll
      for (int i = 0; i < 12; i++) o[i] = 0.f;
      TM(22);
      wg_wait<0>();
    }
    arrive_if(bfull + 160, is_t0);
    TM(24);
    dvt = dv0;
    uint64_t jump = 3 * (R_SLOT / 16);
    uint32_t bst = bfull;
    uint32_t lturn = (wq == 0) ? (hf ? 0x155u : 0x2AAu) : 0u;
#pragma unroll 1
    for (int seg = 0; seg < 2; seg++) {
#pragma unroll 1
      for (int it = 0; it < 5; it++) {
        PIN_S0; PIN_O;
        QK_S1;
        EXP_PV_S0;
        wg_wait<0>();
        const uint32_t oke = mbar_test(bst + 160, 0);
        PIN_S1; PIN_O;
        DESC_ADD(dkt, 384);
        QK_S0;
        EXP_PV_S1;
        if (lturn & 1) {
          mbar_wait_if_not(oke, bst + 160, 0);
          const int st = seg * 5 + it;
          const uint32_t dst = ring + ((st & 1) ^ 1) * 3 * R_SLOT;
          if (st < 9) {
            const int h = (st >= 4), u = rb + 4 + 3 * st + h;
            const uint8_t* hb = kvs + h * 131072;
            elect_load3(dst, hb + (u & 15) * 8192, hb + ((u + 1) & 15) * 8192, hb + ((u + 2) & 15) * 8192, bst + 8);
            if (st == 2) {
              __threadfence();
              if (lane < 2) st_rec(&g_flag[b * 4 + s * 2 + lane], e1, e1, 0u, 0u);
              __syncwarp();
            }
          } else {
            wait_flag_warp(&g_flag[((lane & 7) * 16 + (b >> 3)) * 4 + s * 2].x, e1);
            const uint8_t* so = (const uint8_t*)osrc;
#pragma unroll
            for (int k = 0; k < 6; k += 2) elect_load2(dst + k * 4096, so + k * 16384, dst + k * 4096 + 4096, so + k * 16384 + 16384, 4096, bst + 8, k ? 0 : 24576);
          }
        }
        wg_wait<0>();
        PIN_S0; PIN_O;
        DESC_ADD(dvt, 512);
        QK_S1;
        EXP_PV_S0;
        wg_wait<0>();
        PIN_S1; PIN_O;
        DESC_ADD(dkt, 384);
        QK_S0;
        EXP_PV_S1;
        wg_wait<0>();
        const uint32_t okf = mbar_test(bst + 8, 0);
        PIN_S0; PIN_O;
        DESC_ADD(dvt, 512);
        QK_S1;
        EXP_PV_S0;
        mbar_wait_if_not(okf, bst + 8, 0);
        wg_wait<0>();
        PIN_S1; PIN_O;
        asm volatile("add.s64 %0, %0, %1;\nadd.s64 %0, %0, -1536;" : "+l"(dkt) : "l"(jump));
        QK_S0;
        EXP_PV_S1;
        wg_wait<0>();
        asm volatile("add.s64 %0, %0, %1;\nadd.s64 %0, %0, -1408;\nneg.s64 %1, %1;" : "+l"(dvt), "+l"(jump));
        arrive_if(bst + 168, is_t0);
        bst += 8;
        lturn >>= 1;
        if (it == 0 && seg == 0) TM(25);
      }
      PIN_S0; PIN_O;
      if (seg) break;
      TM(7);
      const uint4 q = lds128(stash), m = lds128(stash + 8192);
      qf[0] = q.x; qf[1] = q.y; qf[2] = q.z; qf[3] = q.w;
      make_qa(qa, __uint_as_float(m.x), __uint_as_float(m.y), t);
      PIN_QA;
      make_c(c0, c1, __uint_as_float(m.x), __uint_as_float(m.y));
      publish_o(o, obase, kvs, stash + 16384, qscr);
      const uint4 v0 = lds128(stash + 24576), v1 = lds128(stash + 32768);
      o[0] = __uint_as_float(v0.x); o[1] = __uint_as_float(v0.y); o[2] = __uint_as_float(v0.z); o[3] = __uint_as_float(v0.w);
      o[4] = __uint_as_float(v1.x); o[5] = __uint_as_float(v1.y); o[6] = __uint_as_float(v1.z); o[7] = __uint_as_float(v1.w);
      o[8] = __uint_as_float(m.z); o[9] = 0.f; o[10] = __uint_as_float(m.w); o[11] = 0.f;
      TM(23);
      PIN_O;
      DESC_ADD(dkt, -128);
      QK_S0;
      wg_wait<0>();
    }
    TM(8);
    publish_o(o, obase + 256, kvs + 131072, stash, qscr);
  }

  {
    const int rc = b >> 3, cc = b & 7;
    const int row0 = rc * 128 + hf * 64 + wq * 16 + g;
    const int col0 = cc * 64 + s * 32 + 2 * t;
    TM(27);
    const uint4* op = osrc + hf * 128 + (tid & 127);
    uint32_t xr[8];
#pragma unroll
    for (int j = 0; j < 4; j++) {
      xr[2 * j] = ld_nc32(x + (size_t)row0 * 512 + col0 + 8 * j);
      xr[2 * j + 1] = ld_nc32(x + (size_t)(row0 + 8) * 512 + col0 + 8 * j);
    }
    const uint4 st0 = ld_rec(&g_rec[row0]), st1 = ld_rec(&g_rec[row0 + 8]);
    uint2 sel2 = ld_tag64(&g_sel);
    uint32_t af[64];
    ld_frag(af + 24, op + 6 * 1024);
    ld_frag(af + 28, op + 7 * 1024);
#pragma unroll
    for (int c = 0; c < 8; c++) ld_frag(af + 32 + 4 * c, op + c * 1024 + 256);
    TM(28);
    mbar_wait(bar + B_WO, 0);
#pragma unroll
    for (int c = 0; c < 6; c++) {
      const uint4 v = lds128(ring + c * 4096 + (tid & 255) * 16);
      af[4 * c] = v.x; af[4 * c + 1] = v.y; af[4 * c + 2] = v.z; af[4 * c + 3] = v.w;
    }
    TM(29);
    float r[16], ro[16];
#pragma unroll
    for (int j = 0; j < 4; j++) {
#pragma unroll
      for (int u = 0; u < 2; u++) {
        const uint32_t nn = ln_apply(xr[2 * j + u], __uint_as_float(u ? st1.x : st0.x), __uint_as_float(u ? st1.y : st0.y));
        r[4 * j + 2 * u] = bf_lo(xr[2 * j + u]) + bf_lo(nn);
        r[4 * j + 2 * u + 1] = bf_hi(xr[2 * j + u]) + bf_hi(nn);
        ro[4 * j + 2 * u] = 0.f; ro[4 * j + 2 * u + 1] = 0.f;
      }
    }
    TM(9);
#pragma unroll
    for (int h2 = 0; h2 < 2; h2++) {
      wait_frags(af + 32 * h2, op + h2 * 256);
      if (h2 == 1) TM(10);
      if (h2 == 0) PIN_R16;
      uint64_t d0 = mkdesc(sb + SM_WO + (s * 2 + h2) * 2048 + s * 64, 16, 1024, 1);
      uint64_t d1 = mkdesc(sb + SM_WO + (s * 2 + h2) * 2048 + (s ^ 1) * 64, 16, 1024, 1);
      wg_fence();
#pragma unroll
      for (int c = 0; c < 8; c++) { wg_rs_n32_t(ro, af + 32 * h2 + 4 * c, d1, 1); DESC_ADD(d1, 512); }
#pragma unroll
      for (int c = 0; c < 8; c++) { wg_rs_n32_t(r, af + 32 * h2 + 4 * c, d0, 1); DESC_ADD(d0, 512); }
      wg_commit();
    }
    const unsigned key = wait_tag64(sel2, &g_sel, e1);
    wg_wait<0>();
    PIN_R16;
    TM(11);
#pragma unroll
    for (int i = 0; i < 4; i++)
      sts128(stash + i * 8192, __float_as_uint(ro[4 * i]), __float_as_uint(ro[4 * i + 1]), __float_as_uint(ro[4 * i + 2]), __float_as_uint(ro[4 * i + 3]));
    bar_sync(7 + hf, 256);
#pragma unroll
    for (int i = 0; i < 4; i++) {
      const uint4 v = lds128(sb + SM_STASH + (tid ^ 256) * 16 + i * 8192);
      r[4 * i] += __uint_as_float(v.x); r[4 * i + 1] += __uint_as_float(v.y);
      r[4 * i + 2] += __uint_as_float(v.z); r[4 * i + 3] += __uint_as_float(v.w);
    }
    const int sel = 2047 - (int)(key & 0xFFFFu);
    if ((sel >> 4) == (row0 >> 4)) {
      const uint32_t rk = key >> 16;
      const float rv = __uint_as_float(((rk & 0x8000u) ? (rk & 0x7FFFu) : (~rk & 0xFFFFu)) << 16);
      const float sg = bf16r(1.0f / (1.0f + expf(-rv)));
      const unsigned long long* yp = g_y + cc * 64 + s * 32 + lane;
      const uint2 y0 = ld_tag64(yp), y1 = ld_tag64(yp + 512), y2 = ld_tag64(yp + 1024), y3 = ld_tag64(yp + 1536);
      float y = __uint_as_float(wait_tag64(y0, yp, e1));
      y += __uint_as_float(wait_tag64(y1, yp + 512, e1));
      y += __uint_as_float(wait_tag64(y2, yp + 1024, e1));
      y += __uint_as_float(wait_tag64(y3, yp + 1536, e1));
      y = bf16r(bf16r(y) * sg);
#pragma unroll
      for (int j = 0; j < 4; j++) {
#pragma unroll
        for (int c = 0; c < 2; c++) {
          const float v = __shfl_sync(0xffffffffu, y, 8 * j + 2 * t + c);
          r[4 * j + c] += (sel == row0) ? v : 0.f;
          r[4 * j + 2 + c] += (sel == row0 + 8) ? v : 0.f;
        }
      }
    }
#pragma unroll
    for (int j = 0; j < 4; j++) {
      *(uint32_t*)(out + (size_t)row0 * 512 + col0 + 8 * j) = pack_bf16(r[4 * j], r[4 * j + 1]);
      *(uint32_t*)(out + (size_t)(row0 + 8) * 512 + col0 + 8 * j) = pack_bf16(r[4 * j + 2], r[4 * j + 3]);
    }
  }
  TM(12); TMG(31);
}

typedef CUresult (*EncodeFn)(CUtensorMap*, CUtensorMapDataType, cuuint32_t, void*, const cuuint64_t*, const cuuint64_t*,
                             const cuuint32_t*, const cuuint32_t*, CUtensorMapInterleave, CUtensorMapSwizzle,
                             CUtensorMapL2promotion, CUtensorMapFloatOOBfill);

}

extern "C" void kernel_launch(void* const* d_in, const int* in_sizes, int n_in, void* d_out, int out_size) {
  (void)in_sizes; (void)n_in; (void)out_size;
  static EncodeFn encode = nullptr;
  if (!encode) {
    void* fn = nullptr;
    cudaDriverEntryPointQueryResult qr;
    cudaGetDriverEntryPoint("cuTensorMapEncodeTiled", &fn, cudaEnableDefault, &qr);
    encode = (EncodeFn)fn;
    cudaFuncSetAttribute(fused_kernel, cudaFuncAttributeMaxDynamicSharedMemorySize, SM_TOTAL);
  }
  CUtensorMap tm_x, tm_wqkv, tm_wo;
  const cuuint32_t es[4] = {1, 1, 1, 1};
  {
    const cuuint64_t dims[2] = {512, 2048};
    const cuuint64_t strides[1] = {1024};
    const cuuint32_t box[2] = {64, 128};
    encode(&tm_x, CU_TENSOR_MAP_DATA_TYPE_BFLOAT16, 2, d_in[0], dims, strides, box, es, CU_TENSOR_MAP_INTERLEAVE_NONE,
           CU_TENSOR_MAP_SWIZZLE_128B, CU_TENSOR_MAP_L2_PROMOTION_L2_128B, CU_TENSOR_MAP_FLOAT_OOB_FILL_NONE);
  }
  {
    const cuuint64_t dims[3] = {512, 512, 3};
    const cuuint64_t strides[2] = {3072, 1024};
    const cuuint32_t box[3] = {64, 64, 3};
    encode(&tm_wqkv, CU_TENSOR_MAP_DATA_TYPE_BFLOAT16, 3, d_in[1], dims, strides, box, es, CU_TENSOR_MAP_INTERLEAVE_NONE,
           CU_TENSOR_MAP_SWIZZLE_128B, CU_TENSOR_MAP_L2_PROMOTION_L2_128B, CU_TENSOR_MAP_FLOAT_OOB_FILL_NONE);
  }
  {
    const cuuint64_t dims[2] = {512, 512};
    const cuuint64_t strides[1] = {1024};
    const cuuint32_t box[2] = {64, 256};
    encode(&tm_wo, CU_TENSOR_MAP_DATA_TYPE_BFLOAT16, 2, d_in[2], dims, strides, box, es, CU_TENSOR_MAP_INTERLEAVE_NONE,
           CU_TENSOR_MAP_SWIZZLE_128B, CU_TENSOR_MAP_L2_PROMOTION_L2_128B, CU_TENSOR_MAP_FLOAT_OOB_FILL_NONE);
  }
  fused_kernel<<<NCTA, 512, SM_TOTAL>>>(tm_x, tm_wqkv, tm_wo, (const __nv_bfloat16*)d_in[0], (const __nv_bfloat16*)d_in[1],
                                        (const __nv_bfloat16*)d_in[4], (const __nv_bfloat16*)d_in[5],
                                        (const __nv_bfloat16*)d_in[6], (const __nv_bfloat16*)d_in[7], (__nv_bfloat16*)d_out);
}
```

```cpp
#include <cuda_runtime.h>
#include <cuda_bf16.h>
#include <cuda.h>
#include <stdint.h>

namespace {

constexpr int NCTA = 132;
constexpr uint32_t A_STAGE = 40960, A_WOFF = 16384;
constexpr uint32_t R_SLOT = 10240, R_STREAM = 61440;
constexpr uint32_t SM_WO = 122880, SM_STASH = 188416, SM_RED = 204800;
constexpr uint32_t SM_AUG = 229376, SM_STAT = 230400, SM_RBAR = 231424, SM_BAR = 232192, SM_MISC = 232320, SM_TOTAL = 232448;
constexpr uint32_t B_FULLA = 0, B_EMPTYA = 64, B_WO = 88, B_S = 104;
constexpr uint32_t RED_REC = 6144, RED_WR = 18432, RED_CS = 20480;
constexpr float M_MARGIN = 104.0f;
constexpr float SC_Q = 0x1p-48f, SC_KM = 0x1p48f, SC_KP = 0x1p-94f;

__device__ __align__(1024) uint8_t g_kv[32 * 16 * 8192];
__device__ uint4 g_o[16 * 32 * 256];
__device__ uint4 g_rec[2048];
__device__ uint4 g_cs[8 * 16 * 64];
__device__ unsigned long long g_y[4 * 512];
__device__ unsigned long long g_sel;
__device__ uint32_t g_qscr[128 * 4 * 512];
__device__ unsigned g_epoch[NCTA * 8];
__device__ uint4 g_flag[128 * 2 * 2];

#define PIN_F(x) asm volatile("" : "+f"(x) :: "memory")
#define PIN_R(x) asm volatile("" : "+r"(x) :: "memory")
#define DESC_ADD(d, n) asm volatile("add.s64 %0, %0, " #n ";" : "+l"(d))

__device__ __forceinline__ void wg_fence() { asm volatile("wgmma.fence.sync.aligned;" ::: "memory"); }
__device__ __forceinline__ void wg_commit() { asm volatile("wgmma.commit_group.sync.aligned;" ::: "memory"); }
template <int N> __device__ __forceinline__ void wg_wait() { asm volatile("wgmma.wait_group.sync.aligned %0;" :: "n"(N) : "memory"); }
__device__ __forceinline__ uint64_t mkdesc(uint32_t a, uint32_t lbo, uint32_t sbo, uint32_t swz) {
  return (uint64_t)((a & 0x3FFFF) >> 4) | ((uint64_t)(lbo >> 4) << 16) | ((uint64_t)(sbo >> 4) << 32) | ((uint64_t)swz << 62);
}
__device__ __forceinline__ void mbar_init(uint32_t a, uint32_t c) { asm volatile("mbarrier.init.shared::cta.b64 [%0], %1;" :: "r"(a), "r"(c) : "memory"); }
__device__ __forceinline__ void mbar_wait(uint32_t a, uint32_t ph) {
  asm volatile("{\n.reg .pred p;\n.reg .u32 n;\nmov.u32 n, 0;\n"
               "W: mbarrier.try_wait.parity.shared::cta.b64 p, [%0], %1;\n@p bra.uni D;\n"
               "add.u32 n, n, 1;\nsetp.lt.u32 p, n, 0x400000;\n@p bra.uni W;\ntrap;\nD:\n}" :: "r"(a), "r"(ph) : "memory");
}
__device__ __forceinline__ uint32_t mbar_test(uint32_t a, uint32_t ph) {
  uint32_t ok;
  asm volatile("{\n.reg .pred p;\nmbarrier.test_wait.parity.shared::cta.b64 p, [%1], %2;\nselp.u32 %0, 1, 0, p;\n}" : "=r"(ok) : "r"(a), "r"(ph) : "memory");
  return ok;
}
__device__ __forceinline__ void mbar_wait_if_not(uint32_t ok, uint32_t a, uint32_t ph) {
  asm volatile("{\n.reg .pred p;\n.reg .u32 n;\nsetp.ne.u32 p, %2, 0;\n@p bra.uni D;\nmov.u32 n, 0;\n"
               "W: mbarrier.try_wait.parity.shared::cta.b64 p, [%0], %1;\n@p bra.uni D;\n"
               "add.u32 n, n, 1;\nsetp.lt.u32 p, n, 0x400000;\n@p bra.uni W;\ntrap;\nD:\n}" :: "r"(a), "r"(ph), "r"(ok) : "memory");
}
__device__ __forceinline__ void wait_flag_warp(const unsigned* p, unsigned target, unsigned first) {
  asm volatile("{\n.reg .pred p;\n.reg .u32 n, v;\nmov.u32 n, 0;\nmov.u32 v, %2;\n"
               "W: sub.s32 v, v, %1;\nsetp.ge.s32 p, v, 0;\nvote.sync.all.pred p, p, 0xffffffff;\n@p bra.uni D;\n"
               "ld.relaxed.gpu.global.u32 v, [%0];\nadd.u32 n, n, 1;\nsetp.lt.u32 p, n, 0x400000;\n@p bra.uni W;\ntrap;\n"
               "D: fence.acquire.gpu;\nfence.proxy.async.global;\n}" :: "l"(p), "r"(target), "r"(first) : "memory");
}
__device__ __forceinline__ void st_tag64(unsigned long long* p, uint32_t v, uint32_t tag) {
  asm volatile("{\n.reg .b64 r;\nmov.b64 r, {%1, %2};\nst.relaxed.gpu.global.b64 [%0], r;\n}" :: "l"(p), "r"(v), "r"(tag) : "memory");
}
__device__ __forceinline__ void st_rec(uint4* p, uint32_t a, uint32_t b, uint32_t c, uint32_t tag) {
  asm volatile("{\n.reg .b64 lo, hi;\n.reg .b128 r;\nmov.b64 lo, {%1, %2};\nmov.b64 hi, {%3, %4};\nmov.b128 r, {lo, hi};\n"
               "st.relaxed.gpu.global.b128 [%0], r;\n}" :: "l"(p), "r"(a), "r"(b), "r"(c), "r"(tag) : "memory");
}
__device__ __forceinline__ uint4 ld_rec(const uint4* p) {
  uint4 v;
  asm volatile("{\n.reg .b64 lo, hi;\n.reg .b128 r;\nld.relaxed.gpu.global.b128 r, [%4];\nmov.b128 {lo, hi}, r;\nmov.b64 {%0, %1}, lo;\nmov.b64 {%2, %3}, hi;\n}"
               : "=r"(v.x), "=r"(v.y), "=r"(v.z), "=r"(v.w) : "l"(p) : "memory");
  return v;
}
__device__ __forceinline__ void wait_rec(uint4& v, const uint4* p, uint32_t tag) {
  asm volatile("{\n.reg .pred p;\n.reg .u32 n;\n.reg .b64 lo, hi;\n.reg .b128 r;\nmov.u32 n, 0;\n"
               "W: setp.eq.u32 p, %3, %5;\nvote.sync.all.pred p, p, 0xffffffff;\n@p bra.uni D;\n"
               "ld.relaxed.gpu.global.b128 r, [%4];\nmov.b128 {lo, hi}, r;\nmov.b64 {%0, %1}, lo;\nmov.b64 {%2, %3}, hi;\n"
               "add.u32 n, n, 1;\nsetp.lt.u32 p, n, 0x400000;\n@p bra.uni W;\ntrap;\nD:\n}"
               : "+r"(v.x), "+r"(v.y), "+r"(v.z), "+r"(v.w) : "l"(p), "r"(tag) : "memory");
}
__device__ __forceinline__ uint2 ld_tag64(const unsigned long long* p) {
  uint2 v;
  asm volatile("{\n.reg .b64 r;\nld.relaxed.gpu.global.b64 r, [%2];\nmov.b64 {%0, %1}, r;\n}" : "=r"(v.x), "=r"(v.y) : "l"(p) : "memory");
  return v;
}
__device__ __forceinline__ uint32_t wait_tag64(uint2 v, const unsigned long long* p, uint32_t tag) {
  asm volatile("{\n.reg .pred p;\n.reg .u32 n;\n.reg .b64 r;\nmov.u32 n, 0;\n"
               "W: setp.eq.u32 p, %1, %3;\nvote.sync.all.pred p, p, 0xffffffff;\n@p bra.uni D;\n"
               "ld.relaxed.gpu.global.b64 r, [%2];\nmov.b64 {%0, %1}, r;\n"
               "add.u32 n, n, 1;\nsetp.lt.u32 p, n, 0x400000;\n@p bra.uni W;\ntrap;\nD:\n}" : "+r"(v.x), "+r"(v.y) : "l"(p), "r"(tag) : "memory");
  return v.x;
}
__device__ __forceinline__ void elect_load2(uint32_t d0, const void* s0, uint32_t d1, const void* s1, uint32_t bytes, uint32_t bar, uint32_t expect) {
  asm volatile("{\n.reg .pred p, q;\nelect.sync _|p, 0xffffffff;\nsetp.ne.and.u32 q, %6, 0, p;\n"
               "@q mbarrier.arrive.expect_tx.shared::cta.b64 _, [%5], %6;\n"
               "@p cp.async.bulk.shared::cluster.global.mbarrier::complete_tx::bytes [%0], [%1], %4, [%5];\n"
               "@p cp.async.bulk.shared::cluster.global.mbarrier::complete_tx::bytes [%2], [%3], %4, [%5];\n}"
               :: "r"(d0), "l"(s0), "r"(d1), "l"(s1), "r"(bytes), "r"(bar), "r"(expect) : "memory");
}
__device__ __forceinline__ void elect_load2v(uint32_t d0, const void* s0, uint32_t n0, uint32_t d1, const void* s1, uint32_t n1, uint32_t bar) {
  asm volatile("{\n.reg .pred p;\n.reg .u32 n;\nelect.sync _|p, 0xffffffff;\nadd.u32 n, %2, %5;\n"
               "@p mbarrier.arrive.expect_tx.shared::cta.b64 _, [%6], n;\n"
               "@p cp.async.bulk.shared::cluster.global.mbarrier::complete_tx::bytes [%0], [%1], %2, [%6];\n"
               "@p cp.async.bulk.shared::cluster.global.mbarrier::complete_tx::bytes [%3], [%4], %5, [%6];\n}"
               :: "r"(d0), "l"(s0), "r"(n0), "r"(d1), "l"(s1), "r"(n1), "r"(bar) : "memory");
}
__device__ __forceinline__ void elect_load_stats(uint32_t dst, const CUtensorMap* mw, int k0, int cg, const void* xrows, uint32_t dwr, const void* wr, uint32_t bar) {
  asm volatile("{\n.reg .pred p;\n.reg .u32 d;\nelect.sync _|p, 0xffffffff;\nadd.u32 d, %0, 16384;\n"
               "@p mbarrier.arrive.expect_tx.shared::cta.b64 _, [%7], 41984;\n"
               "@p cp.async.bulk.shared::cluster.global.mbarrier::complete_tx::bytes [%0], [%4], 16384, [%7];\n"
               "@p cp.async.bulk.shared::cluster.global.mbarrier::complete_tx::bytes [%5], [%6], 1024, [%7];\n"
               "@p cp.async.bulk.tensor.3d.shared::cluster.global.mbarrier::complete_tx::bytes [d], [%1, {%3, %2, 0}], [%7];\n}"
               :: "r"(dst), "l"(mw), "r"(k0), "r"(cg), "l"(xrows), "r"(dwr), "l"(wr), "r"(bar) : "memory");
}
__device__ __forceinline__ void elect_load(uint32_t d, const void* s0, uint32_t bytes, uint32_t bar) {
  asm volatile("{\n.reg .pred p;\nelect.sync _|p, 0xffffffff;\n"
               "@p mbarrier.arrive.expect_tx.shared::cta.b64 _, [%3], %2;\n"
               "@p cp.async.bulk.shared::cluster.global.mbarrier::complete_tx::bytes [%0], [%1], %2, [%3];\n}"
               :: "r"(d), "l"(s0), "r"(bytes), "r"(bar) : "memory");
}
__device__ __forceinline__ void elect_load3(uint32_t d, const void* s0, const void* s1, const void* s2, uint32_t bar) {
  asm volatile("{\n.reg .pred p;\n.reg .u32 d1, d2;\nelect.sync _|p, 0xffffffff;\nadd.u32 d1, %0, 10240;\nadd.u32 d2, %0, 20480;\n"
               "@p mbarrier.arrive.expect_tx.shared::cta.b64 _, [%4], 24576;\n"
               "@p cp.async.bulk.shared::cluster.global.mbarrier::complete_tx::bytes [%0], [%1], 8192, [%4];\n"
               "@p cp.async.bulk.shared::cluster.global.mbarrier::complete_tx::bytes [d1], [%2], 8192, [%4];\n"
               "@p cp.async.bulk.shared::cluster.global.mbarrier::complete_tx::bytes [d2], [%3], 8192, [%4];\n}"
               :: "r"(d), "l"(s0), "l"(s1), "l"(s2), "r"(bar) : "memory");
}
__device__ __forceinline__ void elect_load_ax(uint32_t dst, const CUtensorMap* mw, const CUtensorMap* mx, int k0, int cg, int row, uint32_t bar) {
  asm volatile("{\n.reg .pred p;\n.reg .u32 d;\nelect.sync _|p, 0xffffffff;\nadd.u32 d, %0, 16384;\n"
               "@p mbarrier.arrive.expect_tx.shared::cta.b64 _, [%6], 40960;\n"
               "@p cp.async.bulk.tensor.2d.shared::cluster.global.mbarrier::complete_tx::bytes [%0], [%2, {%3, %5}], [%6];\n"
               "@p cp.async.bulk.tensor.3d.shared::cluster.global.mbarrier::complete_tx::bytes [d], [%1, {%4, %3, 0}], [%6];\n}"
               :: "r"(dst), "l"(mw), "l"(mx), "r"(k0), "r"(cg), "r"(row), "r"(bar) : "memory");
}
__device__ __forceinline__ void elect_tma2d(uint32_t dst, const CUtensorMap* m, int c1, int c2, uint32_t bar, uint32_t expect) {
  asm volatile("{\n.reg .pred p, q;\nelect.sync _|p, 0xffffffff;\nsetp.ne.and.u32 q, %5, 0, p;\n"
               "@q mbarrier.arrive.expect_tx.shared::cta.b64 _, [%4], %5;\n"
               "@p cp.async.bulk.tensor.2d.shared::cluster.global.mbarrier::complete_tx::bytes [%0], [%1, {%2, %3}], [%4];\n}"
               :: "r"(dst), "l"(m), "r"(c1), "r"(c2), "r"(bar), "r"(expect) : "memory");
}
__device__ __forceinline__ void arrive_if(uint32_t a, uint32_t pred) {
  asm volatile("{\n.reg .pred p;\nsetp.ne.u32 p, %1, 0;\n@p mbarrier.arrive.shared::cta.b64 _, [%0];\n}" :: "r"(a), "r"(pred) : "memory");
}
__device__ __forceinline__ void fence_async_smem() { asm volatile("fence.proxy.async.shared::cta;" ::: "memory"); }
#define bar_sync(id, n) asm volatile("bar.sync " #id ", " #n ";" ::: "memory")
#define bar_arrive(id, n) asm volatile("bar.arrive " #id ", " #n ";" ::: "memory")
__device__ __forceinline__ uint32_t pack_bf16(float lo, float hi) { uint32_t r; asm("cvt.rn.bf16x2.f32 %0, %1, %2;" : "=r"(r) : "f"(hi), "f"(lo)); return r; }
__device__ __forceinline__ float bf16r(float x) { return __uint_as_float(pack_bf16(0.f, x) & 0xFFFF0000u); }
__device__ __forceinline__ float bf_lo(uint32_t v) { return __uint_as_float(v << 16); }
__device__ __forceinline__ float bf_hi(uint32_t v) { return __uint_as_float(v & 0xFFFF0000u); }
__device__ __forceinline__ uint32_t nonzero(uint32_t v) { return v ? v : 0x80000000u; }
__device__ __forceinline__ float ex2(float x) { float y; asm("ex2.approx.ftz.f32 %0, %1;" : "=f"(y) : "f"(x)); return y; }
__device__ __forceinline__ void sts32(uint32_t a, uint32_t v) { asm volatile("st.shared.u32 [%0], %1;" :: "r"(a), "r"(v) : "memory"); }
__device__ __forceinline__ void sts128(uint32_t a, uint32_t x, uint32_t y, uint32_t z, uint32_t w) {
  asm volatile("st.shared.v4.u32 [%0], {%1,%2,%3,%4};" :: "r"(a), "r"(x), "r"(y), "r"(z), "r"(w) : "memory");
}
__device__ __forceinline__ uint4 lds128(uint32_t a) {
  uint4 v; asm volatile("ld.shared.v4.u32 {%0,%1,%2,%3}, [%4];" : "=r"(v.x), "=r"(v.y), "=r"(v.z), "=r"(v.w) : "r"(a) : "memory"); return v;
}
__device__ __forceinline__ uint32_t lds32(uint32_t a) { uint32_t v; asm volatile("ld.shared.u32 %0, [%1];" : "=r"(v) : "r"(a) : "memory"); return v; }
__device__ __forceinline__ void stsm4(uint32_t a, uint32_t x, uint32_t y, uint32_t z, uint32_t w) {
  asm volatile("stmatrix.sync.aligned.m8n8.x4.shared.b16 [%0], {%1,%2,%3,%4};" :: "r"(a), "r"(x), "r"(y), "r"(z), "r"(w) : "memory");
}
__device__ __forceinline__ unsigned ld_relaxed(const unsigned* p) {
  unsigned v; asm volatile("ld.relaxed.gpu.global.u32 %0, [%1];" : "=r"(v) : "l"(p) : "memory"); return v;
}
__device__ __forceinline__ void ld_frag(uint32_t* a, const uint4* p) {
  asm volatile("ld.relaxed.gpu.global.v4.u32 {%0,%1,%2,%3}, [%4];" : "=r"(a[0]), "=r"(a[1]), "=r"(a[2]), "=r"(a[3]) : "l"(p) : "memory");
}

__device__ __forceinline__ uint32_t exp2_pair_mufu(float a, float b) { return pack_bf16(ex2(a), ex2(b)); }
__device__ __forceinline__ uint32_t exp2_pair_alu(float a, float b, uint32_t kmant, uint32_t kexpo) {
  uint32_t t, v, e, r;
  asm("cvt.pack.sat.s16.s32 %0, %1, %2;" : "=r"(t) : "r"(__float_as_uint(b)), "r"(__float_as_uint(a)));
  asm("lop3.b32 %0, %1, 0x007F007F, %2, 0xEA;" : "=r"(v) : "r"(t), "r"(kmant));
  asm("lop3.b32 %0, %1, 0x7F807F80, %2, 0xEA;" : "=r"(e) : "r"(t), "r"(kexpo));
  asm("fma.rn.bf16x2 %0, %1, %2, %3;" : "=r"(r) : "r"(t), "r"(v), "r"(e));
  return r;
}

__device__ __forceinline__ void wait_frags8_4(uint32_t* a, const uint4* p) {
  asm volatile("{\n.reg .pred p;\n.reg .u32 n, m<8>, a, b;\nmov.u32 n, 0;\nW:\n"
    "min.u32 a, %0, %1;\nmin.u32 b, %2, %3;\nmin.u32 m0, a, b;\n"
    "min.u32 a, %4, %5;\nmin.u32 b, %6, %7;\nmin.u32 m1, a, b;\n"
    "min.u32 a, %8, %9;\nmin.u32 b, %10, %11;\nmin.u32 m2, a, b;\n"
    "min.u32 a, %12, %13;\nmin.u32 b, %14, %15;\nmin.u32 m3, a, b;\n"
    "min.u32 a, m0, m1;\nmin.u32 a, a, m2;\nmin.u32 a, a, m3;\n"
    "setp.ne.u32 p, a, 0;\nvote.sync.all.pred p, p, 0xffffffff;\n@p bra.uni D;\n"
    "min.u32 a, %16, %17;\nmin.u32 b, %18, %19;\nmin.u32 m4, a, b;\n"
    "min.u32 a, %20, %21;\nmin.u32 b, %22, %23;\nmin.u32 m5, a, b;\n"
    "min.u32 a, %24, %25;\nmin.u32 b, %26, %27;\nmin.u32 m6, a, b;\n"
    "min.u32 a, %28, %29;\nmin.u32 b, %30, %31;\nmin.u32 m7, a, b;\n"
    "setp.eq.u32 p, m0, 0;\n@p ld.relaxed.gpu.global.v4.u32 {%0,%1,%2,%3}, [%32 + 0];\n"
    "setp.eq.u32 p, m1, 0;\n@p ld.relaxed.gpu.global.v4.u32 {%4,%5,%6,%7}, [%32 + 4096];\n"
    "setp.eq.u32 p, m2, 0;\n@p ld.relaxed.gpu.global.v4.u32 {%8,%9,%10,%11}, [%32 + 8192];\n"
    "setp.eq.u32 p, m3, 0;\n@p ld.relaxed.gpu.global.v4.u32 {%12,%13,%14,%15}, [%32 + 12288];\n"
    "setp.eq.u32 p, m4, 0;\n@p ld.relaxed.gpu.global.v4.u32 {%16,%17,%18,%19}, [%32 + 16384];\n"
    "setp.eq.u32 p, m5, 0;\n@p ld.relaxed.gpu.global.v4.u32 {%20,%21,%22,%23}, [%32 + 20480];\n"
    "setp.eq.u32 p, m6, 0;\n@p ld.relaxed.gpu.global.v4.u32 {%24,%25,%26,%27}, [%32 + 24576];\n"
    "setp.eq.u32 p, m7, 0;\n@p ld.relaxed.gpu.global.v4.u32 {%28,%29,%30,%31}, [%32 + 28672];\n"
    "add.u32 n, n, 1;\nsetp.lt.u32 p, n, 0x200000;\n@p bra.uni W;\ntrap;\nD:\n}"
    : "+r"(a[0]),"+r"(a[1]),"+r"(a[2]),"+r"(a[3]),"+r"(a[4]),"+r"(a[5]),"+r"(a[6]),"+r"(a[7]),"+r"(a[8]),"+r"(a[9]),"+r"(a[10]),"+r"(a[11]),"+r"(a[12]),"+r"(a[13]),"+r"(a[14]),"+r"(a[15]),"+r"(a[16]),"+r"(a[17]),"+r"(a[18]),"+r"(a[19]),"+r"(a[20]),"+r"(a[21]),"+r"(a[22]),"+r"(a[23]),"+r"(a[24]),"+r"(a[25]),"+r"(a[26]),"+r"(a[27]),"+r"(a[28]),"+r"(a[29]),"+r"(a[30]),"+r"(a[31])
    : "l"(p) : "memory");
}
__device__ __forceinline__ void wait_cs(uint32_t* a, const uint4* p, uint32_t tag) {
  asm volatile("{\n.reg .b64 lo, hi;\n.reg .b128 r;\n.reg .pred p;\n.reg .u32 n;\nmov.u32 n, 0;\nW:\n"
    "ld.relaxed.gpu.global.b128 r, [%64 + 0];\nmov.b128 {lo, hi}, r;\nmov.b64 {%0, %1}, lo;\nmov.b64 {%2, %3}, hi;\n"
    "ld.relaxed.gpu.global.b128 r, [%64 + 1024];\nmov.b128 {lo, hi}, r;\nmov.b64 {%4, %5}, lo;\nmov.b64 {%6, %7}, hi;\n"
    "ld.relaxed.gpu.global.b128 r, [%64 + 2048];\nmov.b128 {lo, hi}, r;\nmov.b64 {%8, %9}, lo;\nmov.b64 {%10, %11}, hi;\n"
    "ld.relaxed.gpu.global.b128 r, [%64 + 3072];\nmov.b128 {lo, hi}, r;\nmov.b64 {%12, %13}, lo;\nmov.b64 {%14, %15}, hi;\n"
    "ld.relaxed.gpu.global.b128 r, [%64 + 4096];\nmov.b128 {lo, hi}, r;\nmov.b64 {%16, %17}, lo;\nmov.b64 {%18, %19}, hi;\n"
    "ld.relaxed.gpu.global.b128 r, [%64 + 5120];\nmov.b128 {lo, hi}, r;\nmov.b64 {%20, %21}, lo;\nmov.b64 {%22, %23}, hi;\n"
    "ld.relaxed.gpu.global.b128 r, [%64 + 6144];\nmov.b128 {lo, hi}, r;\nmov.b64 {%24, %25}, lo;\nmov.b64 {%26, %27}, hi;\n"
    "ld.relaxed.gpu.global.b128 r, [%64 + 7168];\nmov.b128 {lo, hi}, r;\nmov.b64 {%28, %29}, lo;\nmov.b64 {%30, %31}, hi;\n"
    "ld.relaxed.gpu.global.b128 r, [%64 + 8192];\nmov.b128 {lo, hi}, r;\nmov.b64 {%32, %33}, lo;\nmov.b64 {%34, %35}, hi;\n"
    "ld.relaxed.gpu.global.b128 r, [%64 + 9216];\nmov.b128 {lo, hi}, r;\nmov.b64 {%36, %37}, lo;\nmov.b64 {%38, %39}, hi;\n"
    "ld.relaxed.gpu.global.b128 r, [%64 + 10240];\nmov.b128 {lo, hi}, r;\nmov.b64 {%40, %41}, lo;\nmov.b64 {%42, %43}, hi;\n"
    "ld.relaxed.gpu.global.b128 r, [%64 + 11264];\nmov.b128 {lo, hi}, r;\nmov.b64 {%44, %45}, lo;\nmov.b64 {%46, %47}, hi;\n"
    "ld.relaxed.gpu.global.b128 r, [%64 + 12288];\nmov.b128 {lo, hi}, r;\nmov.b64 {%48, %49}, lo;\nmov.b64 {%50, %51}, hi;\n"
    "ld.relaxed.gpu.global.b128 r, [%64 + 13312];\nmov.b128 {lo, hi}, r;\nmov.b64 {%52, %53}, lo;\nmov.b64 {%54, %55}, hi;\n"
    "ld.relaxed.gpu.global.b128 r, [%64 + 14336];\nmov.b128 {lo, hi}, r;\nmov.b64 {%56, %57}, lo;\nmov.b64 {%58, %59}, hi;\n"
    "ld.relaxed.gpu.global.b128 r, [%64 + 15360];\nmov.b128 {lo, hi}, r;\nmov.b64 {%60, %61}, lo;\nmov.b64 {%62, %63}, hi;\n"
    "setp.eq.u32 p, n, n;\n"
    "setp.eq.and.u32 p, %3, %65, p;\n"
    "setp.eq.and.u32 p, %7, %65, p;\n"
    "setp.eq.and.u32 p, %11, %65, p;\n"
    "setp.eq.and.u32 p, %15, %65, p;\n"
    "setp.eq.and.u32 p, %19, %65, p;\n"
    "setp.eq.and.u32 p, %23, %65, p;\n"
    "setp.eq.and.u32 p, %27, %65, p;\n"
    "setp.eq.and.u32 p, %31, %65, p;\n"
    "setp.eq.and.u32 p, %35, %65, p;\n"
    "setp.eq.and.u32 p, %39, %65, p;\n"
    "setp.eq.and.u32 p, %43, %65, p;\n"
    "setp.eq.and.u32 p, %47, %65, p;\n"
    "setp.eq.and.u32 p, %51, %65, p;\n"
    "setp.eq.and.u32 p, %55, %65, p;\n"
    "setp.eq.and.u32 p, %59, %65, p;\n"
    "setp.eq.and.u32 p, %63, %65, p;\n"
    "vote.sync.all.pred p, p, 0xffffffff;\n@p bra.uni D;\nadd.u32 n, n, 1;\nsetp.lt.u32 p, n, 0x200000;\n@p bra.uni W;\ntrap;\nD:\n}"
    : "=&r"(a[0]),"=&r"(a[1]),"=&r"(a[2]),"=&r"(a[3]),"=&r"(a[4]),"=&r"(a[5]),"=&r"(a[6]),"=&r"(a[7]),"=&r"(a[8]),"=&r"(a[9]),"=&r"(a[10]),"=&r"(a[11]),"=&r"(a[12]),"=&r"(a[13]),"=&r"(a[14]),"=&r"(a[15]),"=&r"(a[16]),"=&r"(a[17]),"=&r"(a[18]),"=&r"(a[19]),"=&r"(a[20]),"=&r"(a[21]),"=&r"(a[22]),"=&r"(a[23]),"=&r"(a[24]),"=&r"(a[25]),"=&r"(a[26]),"=&r"(a[27]),"=&r"(a[28]),"=&r"(a[29]),"=&r"(a[30]),"=&r"(a[31]),"=&r"(a[32]),"=&r"(a[33]),"=&r"(a[34]),"=&r"(a[35]),"=&r"(a[36]),"=&r"(a[37]),"=&r"(a[38]),"=&r"(a[39]),"=&r"(a[40]),"=&r"(a[41]),"=&r"(a[42]),"=&r"(a[43]),"=&r"(a[44]),"=&r"(a[45]),"=&r"(a[46]),"=&r"(a[47]),"=&r"(a[48]),"=&r"(a[49]),"=&r"(a[50]),"=&r"(a[51]),"=&r"(a[52]),"=&r"(a[53]),"=&r"(a[54]),"=&r"(a[55]),"=&r"(a[56]),"=&r"(a[57]),"=&r"(a[58]),"=&r"(a[59]),"=&r"(a[60]),"=&r"(a[61]),"=&r"(a[62]),"=&r"(a[63]) : "l"(p), "r"(tag) : "memory");
}
__device__ __forceinline__ void wait_frags4_4(uint32_t* a, const uint4* p) {
  asm volatile("{\n.reg .pred p;\n.reg .u32 n, m<8>, a, b;\nmov.u32 n, 0;\nW:\n"
    "min.u32 a, %0, %1;\nmin.u32 b, %2, %3;\nmin.u32 m0, a, b;\n"
    "min.u32 a, %4, %5;\nmin.u32 b, %6, %7;\nmin.u32 m1, a, b;\n"
    "min.u32 a, %8, %9;\nmin.u32 b, %10, %11;\nmin.u32 m2, a, b;\n"
    "min.u32 a, %12, %13;\nmin.u32 b, %14, %15;\nmin.u32 m3, a, b;\n"
    "min.u32 a, m0, m1;\nmin.u32 a, a, m2;\nmin.u32 a, a, m3;\n"
    "setp.ne.u32 p, a, 0;\nvote.sync.all.pred p, p, 0xffffffff;\n@p bra.uni D;\n"
    "setp.eq.u32 p, m0, 0;\n@p ld.relaxed.gpu.global.v4.u32 {%0,%1,%2,%3}, [%16 + 0];\n"
    "setp.eq.u32 p, m1, 0;\n@p ld.relaxed.gpu.global.v4.u32 {%4,%5,%6,%7}, [%16 + 4096];\n"
    "setp.eq.u32 p, m2, 0;\n@p ld.relaxed.gpu.global.v4.u32 {%8,%9,%10,%11}, [%16 + 8192];\n"
    "setp.eq.u32 p, m3, 0;\n@p ld.relaxed.gpu.global.v4.u32 {%12,%13,%14,%15}, [%16 + 12288];\n"
    "add.u32 n, n, 1;\nsetp.lt.u32 p, n, 0x200000;\n@p bra.uni W;\ntrap;\nD:\n}"
    : "+r"(a[0]),"+r"(a[1]),"+r"(a[2]),"+r"(a[3]),"+r"(a[4]),"+r"(a[5]),"+r"(a[6]),"+r"(a[7]),"+r"(a[8]),"+r"(a[9]),"+r"(a[10]),"+r"(a[11]),"+r"(a[12]),"+r"(a[13]),"+r"(a[14]),"+r"(a[15])
    : "l"(p) : "memory");
}
__device__ __forceinline__ void wg_ss_n192_t(float* d, uint64_t da, uint64_t db, int sd) {
  asm volatile("{\n.reg .pred p;\nsetp.ne.b32 p, %98, 0;\n"
    "wgmma.mma_async.sync.aligned.m64n192k16.f32.bf16.bf16 {%0,%1,%2,%3,%4,%5,%6,%7,%8,%9,%10,%11,%12,%13,%14,%15,%16,%17,%18,%19,%20,%21,%22,%23,%24,%25,%26,%27,%28,%29,%30,%31,%32,%33,%34,%35,%36,%37,%38,%39,%40,%41,%42,%43,%44,%45,%46,%47,%48,%49,%50,%51,%52,%53,%54,%55,%56,%57,%58,%59,%60,%61,%62,%63,%64,%65,%66,%67,%68,%69,%70,%71,%72,%73,%74,%75,%76,%77,%78,%79,%80,%81,%82,%83,%84,%85,%86,%87,%88,%89,%90,%91,%92,%93,%94,%95}, %96, %97, p, 1, 1, 0, 1;\n}\n"
    : "+f"(d[0]),"+f"(d[1]),"+f"(d[2]),"+f"(d[3]),"+f"(d[4]),"+f"(d[5]),"+f"(d[6]),"+f"(d[7]),"+f"(d[8]),"+f"(d[9]),"+f"(d[10]),"+f"(d[11]),"+f"(d[12]),"+f"(d[13]),"+f"(d[14]),"+f"(d[15]),"+f"(d[16]),"+f"(d[17]),"+f"(d[18]),"+f"(d[19]),"+f"(d[20]),"+f"(d[21]),"+f"(d[22]),"+f"(d[23]),"+f"(d[24]),"+f"(d[25]),"+f"(d[26]),"+f"(d[27]),"+f"(d[28]),"+f"(d[29]),"+f"(d[30]),"+f"(d[31]),"+f"(d[32]),"+f"(d[33]),"+f"(d[34]),"+f"(d[35]),"+f"(d[36]),"+f"(d[37]),"+f"(d[38]),"+f"(d[39]),"+f"(d[40]),"+f"(d[41]),"+f"(d[42]),"+f"(d[43]),"+f"(d[44]),"+f"(d[45]),"+f"(d[46]),"+f"(d[47]),"+f"(d[48]),"+f"(d[49]),"+f"(d[50]),"+f"(d[51]),"+f"(d[52]),"+f"(d[53]),"+f"(d[54]),"+f"(d[55]),"+f"(d[56]),"+f"(d[57]),"+f"(d[58]),"+f"(d[59]),"+f"(d[60]),"+f"(d[61]),"+f"(d[62]),"+f"(d[63]),"+f"(d[64]),"+f"(d[65]),"+f"(d[66]),"+f"(d[67]),"+f"(d[68]),"+f"(d[69]),"+f"(d[70]),"+f"(d[71]),"+f"(d[72]),"+f"(d[73]),"+f"(d[74]),"+f"(d[75]),"+f"(d[76]),"+f"(d[77]),"+f"(d[78]),"+f"(d[79]),"+f"(d[80]),"+f"(d[81]),"+f"(d[82]),"+f"(d[83]),"+f"(d[84]),"+f"(d[85]),"+f"(d[86]),"+f"(d[87]),"+f"(d[88]),"+f"(d[89]),"+f"(d[90]),"+f"(d[91]),"+f"(d[92]),"+f"(d[93]),"+f"(d[94]),"+f"(d[95])
    : "l"(da), "l"(db), "r"(sd));
}
__device__ __forceinline__ void wg_rs_n64_t(float* d, const uint32_t* a, uint64_t db, int sd) {
  asm volatile("{\n.reg .pred p;\nsetp.ne.b32 p, %37, 0;\n"
    "wgmma.mma_async.sync.aligned.m64n64k16.f32.bf16.bf16 {%0,%1,%2,%3,%4,%5,%6,%7,%8,%9,%10,%11,%12,%13,%14,%15,%16,%17,%18,%19,%20,%21,%22,%23,%24,%25,%26,%27,%28,%29,%30,%31}, {%32,%33,%34,%35}, %36, p, 1, 1, 1;\n}\n"
    : "+f"(d[0]),"+f"(d[1]),"+f"(d[2]),"+f"(d[3]),"+f"(d[4]),"+f"(d[5]),"+f"(d[6]),"+f"(d[7]),"+f"(d[8]),"+f"(d[9]),"+f"(d[10]),"+f"(d[11]),"+f"(d[12]),"+f"(d[13]),"+f"(d[14]),"+f"(d[15]),"+f"(d[16]),"+f"(d[17]),"+f"(d[18]),"+f"(d[19]),"+f"(d[20]),"+f"(d[21]),"+f"(d[22]),"+f"(d[23]),"+f"(d[24]),"+f"(d[25]),"+f"(d[26]),"+f"(d[27]),"+f"(d[28]),"+f"(d[29]),"+f"(d[30]),"+f"(d[31])
    : "r"(a[0]),"r"(a[1]),"r"(a[2]),"r"(a[3]), "l"(db), "r"(sd));
}
__device__ __forceinline__ void wg_ss_n64_t(float* d, uint64_t da, uint64_t db, int sd) {
  asm volatile("{\n.reg .pred p;\nsetp.ne.b32 p, %34, 0;\n"
    "wgmma.mma_async.sync.aligned.m64n64k16.f32.bf16.bf16 {%0,%1,%2,%3,%4,%5,%6,%7,%8,%9,%10,%11,%12,%13,%14,%15,%16,%17,%18,%19,%20,%21,%22,%23,%24,%25,%26,%27,%28,%29,%30,%31}, %32, %33, p, 1, 1, 0, 1;\n}\n"
    : "+f"(d[0]),"+f"(d[1]),"+f"(d[2]),"+f"(d[3]),"+f"(d[4]),"+f"(d[5]),"+f"(d[6]),"+f"(d[7]),"+f"(d[8]),"+f"(d[9]),"+f"(d[10]),"+f"(d[11]),"+f"(d[12]),"+f"(d[13]),"+f"(d[14]),"+f"(d[15]),"+f"(d[16]),"+f"(d[17]),"+f"(d[18]),"+f"(d[19]),"+f"(d[20]),"+f"(d[21]),"+f"(d[22]),"+f"(d[23]),"+f"(d[24]),"+f"(d[25]),"+f"(d[26]),"+f"(d[27]),"+f"(d[28]),"+f"(d[29]),"+f"(d[30]),"+f"(d[31])
    : "l"(da), "l"(db), "r"(sd));
}
__device__ __forceinline__ void wg_rs_n192(float* d, const uint32_t* a, uint64_t db, int sd) {
  asm volatile("{\n.reg .pred p;\nsetp.ne.b32 p, %101, 0;\n"
    "wgmma.mma_async.sync.aligned.m64n192k16.f32.bf16.bf16 {%0,%1,%2,%3,%4,%5,%6,%7,%8,%9,%10,%11,%12,%13,%14,%15,%16,%17,%18,%19,%20,%21,%22,%23,%24,%25,%26,%27,%28,%29,%30,%31,%32,%33,%34,%35,%36,%37,%38,%39,%40,%41,%42,%43,%44,%45,%46,%47,%48,%49,%50,%51,%52,%53,%54,%55,%56,%57,%58,%59,%60,%61,%62,%63,%64,%65,%66,%67,%68,%69,%70,%71,%72,%73,%74,%75,%76,%77,%78,%79,%80,%81,%82,%83,%84,%85,%86,%87,%88,%89,%90,%91,%92,%93,%94,%95}, {%96,%97,%98,%99}, %100, p, 1, 1, 0;\n}\n"
    : "+f"(d[0]),"+f"(d[1]),"+f"(d[2]),"+f"(d[3]),"+f"(d[4]),"+f"(d[5]),"+f"(d[6]),"+f"(d[7]),"+f"(d[8]),"+f"(d[9]),"+f"(d[10]),"+f"(d[11]),"+f"(d[12]),"+f"(d[13]),"+f"(d[14]),"+f"(d[15]),"+f"(d[16]),"+f"(d[17]),"+f"(d[18]),"+f"(d[19]),"+f"(d[20]),"+f"(d[21]),"+f"(d[22]),"+f"(d[23]),"+f"(d[24]),"+f"(d[25]),"+f"(d[26]),"+f"(d[27]),"+f"(d[28]),"+f"(d[29]),"+f"(d[30]),"+f"(d[31]),"+f"(d[32]),"+f"(d[33]),"+f"(d[34]),"+f"(d[35]),"+f"(d[36]),"+f"(d[37]),"+f"(d[38]),"+f"(d[39]),"+f"(d[40]),"+f"(d[41]),"+f"(d[42]),"+f"(d[43]),"+f"(d[44]),"+f"(d[45]),"+f"(d[46]),"+f"(d[47]),"+f"(d[48]),"+f"(d[49]),"+f"(d[50]),"+f"(d[51]),"+f"(d[52]),"+f"(d[53]),"+f"(d[54]),"+f"(d[55]),"+f"(d[56]),"+f"(d[57]),"+f"(d[58]),"+f"(d[59]),"+f"(d[60]),"+f"(d[61]),"+f"(d[62]),"+f"(d[63]),"+f"(d[64]),"+f"(d[65]),"+f"(d[66]),"+f"(d[67]),"+f"(d[68]),"+f"(d[69]),"+f"(d[70]),"+f"(d[71]),"+f"(d[72]),"+f"(d[73]),"+f"(d[74]),"+f"(d[75]),"+f"(d[76]),"+f"(d[77]),"+f"(d[78]),"+f"(d[79]),"+f"(d[80]),"+f"(d[81]),"+f"(d[82]),"+f"(d[83]),"+f"(d[84]),"+f"(d[85]),"+f"(d[86]),"+f"(d[87]),"+f"(d[88]),"+f"(d[89]),"+f"(d[90]),"+f"(d[91]),"+f"(d[92]),"+f"(d[93]),"+f"(d[94]),"+f"(d[95])
    : "r"(a[0]),"r"(a[1]),"r"(a[2]),"r"(a[3]), "l"(db), "r"(sd));
}
__device__ __forceinline__ void wg_rs_n64(float* d, const uint32_t* a, uint64_t db, int sd) {
  asm volatile("{\n.reg .pred p;\nsetp.ne.b32 p, %37, 0;\n"
    "wgmma.mma_async.sync.aligned.m64n64k16.f32.bf16.bf16 {%0,%1,%2,%3,%4,%5,%6,%7,%8,%9,%10,%11,%12,%13,%14,%15,%16,%17,%18,%19,%20,%21,%22,%23,%24,%25,%26,%27,%28,%29,%30,%31}, {%32,%33,%34,%35}, %36, p, 1, 1, 0;\n}\n"
    : "+f"(d[0]),"+f"(d[1]),"+f"(d[2]),"+f"(d[3]),"+f"(d[4]),"+f"(d[5]),"+f"(d[6]),"+f"(d[7]),"+f"(d[8]),"+f"(d[9]),"+f"(d[10]),"+f"(d[11]),"+f"(d[12]),"+f"(d[13]),"+f"(d[14]),"+f"(d[15]),"+f"(d[16]),"+f"(d[17]),"+f"(d[18]),"+f"(d[19]),"+f"(d[20]),"+f"(d[21]),"+f"(d[22]),"+f"(d[23]),"+f"(d[24]),"+f"(d[25]),"+f"(d[26]),"+f"(d[27]),"+f"(d[28]),"+f"(d[29]),"+f"(d[30]),"+f"(d[31])
    : "r"(a[0]),"r"(a[1]),"r"(a[2]),"r"(a[3]), "l"(db), "r"(sd));
}
__device__ __forceinline__ void wg_rs_n24_t(float* d, const uint32_t* a, uint64_t db, int sd) {
  asm volatile("{\n.reg .pred p;\nsetp.ne.b32 p, %17, 0;\n"
    "wgmma.mma_async.sync.aligned.m64n24k16.f32.bf16.bf16 {%0,%1,%2,%3,%4,%5,%6,%7,%8,%9,%10,%11}, {%12,%13,%14,%15}, %16, p, 1, 1, 1;\n}\n"
    : "+f"(d[0]),"+f"(d[1]),"+f"(d[2]),"+f"(d[3]),"+f"(d[4]),"+f"(d[5]),"+f"(d[6]),"+f"(d[7]),"+f"(d[8]),"+f"(d[9]),"+f"(d[10]),"+f"(d[11])
    : "r"(a[0]),"r"(a[1]),"r"(a[2]),"r"(a[3]), "l"(db), "r"(sd));
}
#define KPERM 0x27160543u
#define NMUFU 24
#define TILE_S0(HOOK) do { \
  wg_fence(); \
  wg_rs_n64(s1, qf, dkt, 0); DESC_ADD(dkt, 128); \
  HOOK; \
  wg_rs_n64(s1, qa, daug, 1); \
  pr[0] = exp2_pair_alu(s0[12], s0[13], kmant, kexpo); \
  pr[1] = exp2_pair_alu(s0[14], s0[15], kmant, kexpo); \
  pr[2] = exp2_pair_alu(s0[16], s0[17], kmant, kexpo); \
  pr[3] = exp2_pair_alu(s0[18], s0[19], kmant, kexpo); \
  PIN_R(pr[0]); \
  PIN_R(pr[1]); \
  PIN_R(pr[2]); \
  PIN_R(pr[3]); \
  pr[4] = exp2_pair_alu(s0[20], s0[21], kmant, kexpo); \
  pr[5] = exp2_pair_alu(s0[22], s0[23], kmant, kexpo); \
  pr[6] = exp2_pair_mufu(s0[0], s0[1]); \
  pr[7] = exp2_pair_mufu(s0[2], s0[3]); \
  PIN_R(pr[4]); \
  PIN_R(pr[5]); \
  PIN_R(pr[6]); \
  PIN_R(pr[7]); \
  wg_fence(); \
  wg_rs_n24_t(o, pr + 0, dvt + 0, 1); \
  wg_rs_n24_t(o, pr + 4, dvt + 16, 1); \
  pr[8] = exp2_pair_alu(s0[24], s0[25], kmant, kexpo); \
  pr[9] = exp2_pair_alu(s0[26], s0[27], kmant, kexpo); \
  pr[10] = exp2_pair_mufu(s0[4], s0[5]); \
  pr[11] = exp2_pair_mufu(s0[6], s0[7]); \
  PIN_R(pr[8]); \
  PIN_R(pr[9]); \
  PIN_R(pr[10]); \
  PIN_R(pr[11]); \
  wg_fence(); \
  wg_rs_n24_t(o, pr + 8, dvt + 32, 1); \
  pr[12] = exp2_pair_alu(s0[28], s0[29], kmant, kexpo); \
  pr[13] = exp2_pair_alu(s0[30], s0[31], kmant, kexpo); \
  pr[14] = exp2_pair_mufu(s0[8], s0[9]); \
  pr[15] = exp2_pair_mufu(s0[10], s0[11]); \
  PIN_R(pr[12]); \
  PIN_R(pr[13]); \
  PIN_R(pr[14]); \
  PIN_R(pr[15]); \
  wg_fence(); \
  wg_rs_n24_t(o, pr + 12, dvt + 48, 1); \
  DESC_ADD(dvt, 64); \
  wg_commit(); \
} while (0)
#define PIN_S0 do { \
  PIN_F(s0[0]); \
  PIN_F(s0[1]); \
  PIN_F(s0[2]); \
  PIN_F(s0[3]); \
  PIN_F(s0[4]); \
  PIN_F(s0[5]); \
  PIN_F(s0[6]); \
  PIN_F(s0[7]); \
  PIN_F(s0[8]); \
  PIN_F(s0[9]); \
  PIN_F(s0[10]); \
  PIN_F(s0[11]); \
  PIN_F(s0[12]); \
  PIN_F(s0[13]); \
  PIN_F(s0[14]); \
  PIN_F(s0[15]); \
  PIN_F(s0[16]); \
  PIN_F(s0[17]); \
  PIN_F(s0[18]); \
  PIN_F(s0[19]); \
  PIN_F(s0[20]); \
  PIN_F(s0[21]); \
  PIN_F(s0[22]); \
  PIN_F(s0[23]); \
  PIN_F(s0[24]); \
  PIN_F(s0[25]); \
  PIN_F(s0[26]); \
  PIN_F(s0[27]); \
  PIN_F(s0[28]); \
  PIN_F(s0[29]); \
  PIN_F(s0[30]); \
  PIN_F(s0[31]); \
} while (0)
#define TILE_S1(HOOK) do { \
  wg_fence(); \
  wg_rs_n64(s0, qf, dkt, 0); DESC_ADD(dkt, 128); \
  HOOK; \
  wg_rs_n64(s0, qa, daug, 1); \
  pr[0] = exp2_pair_alu(s1[12], s1[13], kmant, kexpo); \
  pr[1] = exp2_pair_alu(s1[14], s1[15], kmant, kexpo); \
  pr[2] = exp2_pair_alu(s1[16], s1[17], kmant, kexpo); \
  pr[3] = exp2_pair_alu(s1[18], s1[19], kmant, kexpo); \
  PIN_R(pr[0]); \
  PIN_R(pr[1]); \
  PIN_R(pr[2]); \
  PIN_R(pr[3]); \
  pr[4] = exp2_pair_alu(s1[20], s1[21], kmant, kexpo); \
  pr[5] = exp2_pair_alu(s1[22], s1[23], kmant, kexpo); \
  pr[6] = exp2_pair_mufu(s1[0], s1[1]); \
  pr[7] = exp2_pair_mufu(s1[2], s1[3]); \
  PIN_R(pr[4]); \
  PIN_R(pr[5]); \
  PIN_R(pr[6]); \
  PIN_R(pr[7]); \
  wg_fence(); \
  wg_rs_n24_t(o, pr + 0, dvt + 0, 1); \
  wg_rs_n24_t(o, pr + 4, dvt + 16, 1); \
  pr[8] = exp2_pair_alu(s1[24], s1[25], kmant, kexpo); \
  pr[9] = exp2_pair_alu(s1[26], s1[27], kmant, kexpo); \
  pr[10] = exp2_pair_mufu(s1[4], s1[5]); \
  pr[11] = exp2_pair_mufu(s1[6], s1[7]); \
  PIN_R(pr[8]); \
  PIN_R(pr[9]); \
  PIN_R(pr[10]); \
  PIN_R(pr[11]); \
  wg_fence(); \
  wg_rs_n24_t(o, pr + 8, dvt + 32, 1); \
  pr[12] = exp2_pair_alu(s1[28], s1[29], kmant, kexpo); \
  pr[13] = exp2_pair_alu(s1[30], s1[31], kmant, kexpo); \
  pr[14] = exp2_pair_mufu(s1[8], s1[9]); \
  pr[15] = exp2_pair_mufu(s1[10], s1[11]); \
  PIN_R(pr[12]); \
  PIN_R(pr[13]); \
  PIN_R(pr[14]); \
  PIN_R(pr[15]); \
  wg_fence(); \
  wg_rs_n24_t(o, pr + 12, dvt + 48, 1); \
  DESC_ADD(dvt, 64); \
  wg_commit(); \
} while (0)
#define PIN_S1 do { \
  PIN_F(s1[0]); \
  PIN_F(s1[1]); \
  PIN_F(s1[2]); \
  PIN_F(s1[3]); \
  PIN_F(s1[4]); \
  PIN_F(s1[5]); \
  PIN_F(s1[6]); \
  PIN_F(s1[7]); \
  PIN_F(s1[8]); \
  PIN_F(s1[9]); \
  PIN_F(s1[10]); \
  PIN_F(s1[11]); \
  PIN_F(s1[12]); \
  PIN_F(s1[13]); \
  PIN_F(s1[14]); \
  PIN_F(s1[15]); \
  PIN_F(s1[16]); \
  PIN_F(s1[17]); \
  PIN_F(s1[18]); \
  PIN_F(s1[19]); \
  PIN_F(s1[20]); \
  PIN_F(s1[21]); \
  PIN_F(s1[22]); \
  PIN_F(s1[23]); \
  PIN_F(s1[24]); \
  PIN_F(s1[25]); \
  PIN_F(s1[26]); \
  PIN_F(s1[27]); \
  PIN_F(s1[28]); \
  PIN_F(s1[29]); \
  PIN_F(s1[30]); \
  PIN_F(s1[31]); \
} while (0)
#define QK_S0 do { \
  wg_fence(); \
  wg_rs_n64(s0, qf, dkt, 0); wg_rs_n64(s0, qa, daug, 1); DESC_ADD(dkt, 128); \
  wg_commit(); \
} while (0)
#define PIN_O do { \
  PIN_F(o[0]); \
  PIN_F(o[1]); \
  PIN_F(o[2]); \
  PIN_F(o[3]); \
  PIN_F(o[4]); \
  PIN_F(o[5]); \
  PIN_F(o[6]); \
  PIN_F(o[7]); \
  PIN_F(o[8]); \
  PIN_F(o[9]); \
  PIN_F(o[10]); \
  PIN_F(o[11]); \
} while (0)
#define PIN_ACC96 do { \
  PIN_F(acc[0]); \
  PIN_F(acc[1]); \
  PIN_F(acc[2]); \
  PIN_F(acc[3]); \
  PIN_F(acc[4]); \
  PIN_F(acc[5]); \
  PIN_F(acc[6]); \
  PIN_F(acc[7]); \
  PIN_F(acc[8]); \
  PIN_F(acc[9]); \
  PIN_F(acc[10]); \
  PIN_F(acc[11]); \
  PIN_F(acc[12]); \
  PIN_F(acc[13]); \
  PIN_F(acc[14]); \
  PIN_F(acc[15]); \
  PIN_F(acc[16]); \
  PIN_F(acc[17]); \
  PIN_F(acc[18]); \
  PIN_F(acc[19]); \
  PIN_F(acc[20]); \
  PIN_F(acc[21]); \
  PIN_F(acc[22]); \
  PIN_F(acc[23]); \
  PIN_F(acc[24]); \
  PIN_F(acc[25]); \
  PIN_F(acc[26]); \
  PIN_F(acc[27]); \
  PIN_F(acc[28]); \
  PIN_F(acc[29]); \
  PIN_F(acc[30]); \
  PIN_F(acc[31]); \
  PIN_F(acc[32]); \
  PIN_F(acc[33]); \
  PIN_F(acc[34]); \
  PIN_F(acc[35]); \
  PIN_F(acc[36]); \
  PIN_F(acc[37]); \
  PIN_F(acc[38]); \
  PIN_F(acc[39]); \
  PIN_F(acc[40]); \
  PIN_F(acc[41]); \
  PIN_F(acc[42]); \
  PIN_F(acc[43]); \
  PIN_F(acc[44]); \
  PIN_F(acc[45]); \
  PIN_F(acc[46]); \
  PIN_F(acc[47]); \
  PIN_F(acc[48]); \
  PIN_F(acc[49]); \
  PIN_F(acc[50]); \
  PIN_F(acc[51]); \
  PIN_F(acc[52]); \
  PIN_F(acc[53]); \
  PIN_F(acc[54]); \
  PIN_F(acc[55]); \
  PIN_F(acc[56]); \
  PIN_F(acc[57]); \
  PIN_F(acc[58]); \
  PIN_F(acc[59]); \
  PIN_F(acc[60]); \
  PIN_F(acc[61]); \
  PIN_F(acc[62]); \
  PIN_F(acc[63]); \
  PIN_F(acc[64]); \
  PIN_F(acc[65]); \
  PIN_F(acc[66]); \
  PIN_F(acc[67]); \
  PIN_F(acc[68]); \
  PIN_F(acc[69]); \
  PIN_F(acc[70]); \
  PIN_F(acc[71]); \
  PIN_F(acc[72]); \
  PIN_F(acc[73]); \
  PIN_F(acc[74]); \
  PIN_F(acc[75]); \
  PIN_F(acc[76]); \
  PIN_F(acc[77]); \
  PIN_F(acc[78]); \
  PIN_F(acc[79]); \
  PIN_F(acc[80]); \
  PIN_F(acc[81]); \
  PIN_F(acc[82]); \
  PIN_F(acc[83]); \
  PIN_F(acc[84]); \
  PIN_F(acc[85]); \
  PIN_F(acc[86]); \
  PIN_F(acc[87]); \
  PIN_F(acc[88]); \
  PIN_F(acc[89]); \
  PIN_F(acc[90]); \
  PIN_F(acc[91]); \
  PIN_F(acc[92]); \
  PIN_F(acc[93]); \
  PIN_F(acc[94]); \
  PIN_F(acc[95]); \
} while (0)
#define PIN_ACC32 do { \
  PIN_F(acc2[0]); \
  PIN_F(acc2[1]); \
  PIN_F(acc2[2]); \
  PIN_F(acc2[3]); \
  PIN_F(acc2[4]); \
  PIN_F(acc2[5]); \
  PIN_F(acc2[6]); \
  PIN_F(acc2[7]); \
  PIN_F(acc2[8]); \
  PIN_F(acc2[9]); \
  PIN_F(acc2[10]); \
  PIN_F(acc2[11]); \
  PIN_F(acc2[12]); \
  PIN_F(acc2[13]); \
  PIN_F(acc2[14]); \
  PIN_F(acc2[15]); \
  PIN_F(acc2[16]); \
  PIN_F(acc2[17]); \
  PIN_F(acc2[18]); \
  PIN_F(acc2[19]); \
  PIN_F(acc2[20]); \
  PIN_F(acc2[21]); \
  PIN_F(acc2[22]); \
  PIN_F(acc2[23]); \
  PIN_F(acc2[24]); \
  PIN_F(acc2[25]); \
  PIN_F(acc2[26]); \
  PIN_F(acc2[27]); \
  PIN_F(acc2[28]); \
  PIN_F(acc2[29]); \
  PIN_F(acc2[30]); \
  PIN_F(acc2[31]); \
} while (0)
#define PIN_QA do { \
  PIN_R(qa[0]); \
  PIN_R(qa[1]); \
  PIN_R(qa[2]); \
  PIN_R(qa[3]); \
  PIN_R(qf[0]); \
  PIN_R(qf[1]); \
  PIN_R(qf[2]); \
  PIN_R(qf[3]); \
} while (0)


__device__ __forceinline__ void ln_partial(const uint4& xa, const uint4& xb, const float* w, float* v) {
  const uint32_t xw[8] = {xa.x, xa.y, xa.z, xa.w, xb.x, xb.y, xb.z, xb.w};
  float sum = 0.f, sq = 0.f, dot = 0.f;
#pragma unroll
  for (int i = 0; i < 8; i++) {
    const float a = bf_lo(xw[i]), c = bf_hi(xw[i]);
    sum += a + c;
    sq = fmaf(a, a, fmaf(c, c, sq));
    dot = fmaf(a, w[2 * i], fmaf(c, w[2 * i + 1], dot));
  }
  v[0] = sum; v[1] = sq; v[2] = dot;
}
__device__ __forceinline__ float warp_sum8(const float* v, int lane) {
  float a[4], b[2], c;
#pragma unroll
  for (int i = 0; i < 4; i++) a[i] = ((lane & 16) ? v[4 + i] : v[i]) + __shfl_xor_sync(0xffffffffu, (lane & 16) ? v[i] : v[4 + i], 16);
#pragma unroll
  for (int i = 0; i < 2; i++) b[i] = ((lane & 8) ? a[2 + i] : a[i]) + __shfl_xor_sync(0xffffffffu, (lane & 8) ? a[i] : a[2 + i], 8);
  c = ((lane & 4) ? b[1] : b[0]) + __shfl_xor_sync(0xffffffffu, (lane & 4) ? b[0] : b[1], 4);
  c += __shfl_xor_sync(0xffffffffu, c, 2);
  return c + __shfl_xor_sync(0xffffffffu, c, 1);
}
__device__ __forceinline__ uint32_t ln_apply(uint32_t v, float mb, float rs) {
  const uint32_t d = pack_bf16(bf_lo(v) - mb, bf_hi(v) - mb);
  return pack_bf16(bf_lo(d) * rs, bf_hi(d) * rs);
}

__device__ __noinline__ void attn_fallback(uint32_t q0, uint32_t q1, uint32_t q2, uint32_t q3, const uint8_t* kvh,
                                           uint32_t* odst, uint32_t* qscr, int tile) {
  const int lane = threadIdx.x & 31, g = lane >> 2, t = lane & 3;
  qscr[g * 8 + t] = q0;
  qscr[(g + 8) * 8 + t] = q1;
  qscr[g * 8 + 4 + t] = q2;
  qscr[(g + 8) * 8 + 4 + t] = q3;
  __threadfence();
  __syncwarp();
  const int row = lane >> 1, par = lane & 1;
  float q[16], o[16];
#pragma unroll
  for (int i = 0; i < 8; i++) { uint32_t v = __ldcg(qscr + row * 8 + i); q[2 * i] = bf_lo(v) * SC_KM; q[2 * i + 1] = bf_hi(v) * SC_KM; }
#pragma unroll
  for (int i = 0; i < 16; i++) o[i] = 0.f;
  float m = -INFINITY, l = 0.f;
#pragma unroll 1
  for (int key = par * 1024; key < par * 1024 + 1024; key++) {
    const int blk = key >> 7, kk = key & 127, G = kk >> 3;
    const int pos = (KPERM >> (4 * (G & 7))) & 7;
    const float ks = (pos < NMUFU / 8) ? SC_Q : 0x1p94f;
    const uint8_t* kp = kvh + blk * 8192 + (G >> 3) * 2048 + pos * 256 + (kk & 7) * 16;
    const uint8_t* vp = kvh + blk * 8192 + 4096 + kk * 16;
    const uint4 k0 = __ldcg((const uint4*)kp), k1 = __ldcg((const uint4*)(kp + 128));
    const uint4 v0 = __ldcg((const uint4*)vp), v1 = __ldcg((const uint4*)(vp + 2048));
    const uint32_t kw[8] = {k0.x, k0.y, k0.z, k0.w, k1.x, k1.y, k1.z, k1.w};
    const uint32_t vw[8] = {v0.x, v0.y, v0.z, v0.w, v1.x, v1.y, v1.z, v1.w};
    float s = 0.f;
#pragma unroll
    for (int i = 0; i < 8; i++) { s = fmaf(q[2 * i], bf_lo(kw[i]) * ks, s); s = fmaf(q[2 * i + 1], bf_hi(kw[i]) * ks, s); }
    if (s == -INFINITY) continue;
    const float mn = fmaxf(m, s), a = exp2f(m - mn), p = exp2f(s - mn);
    m = mn;
    l = l * a + p;
#pragma unroll
    for (int i = 0; i < 8; i++) { o[2 * i] = o[2 * i] * a + p * bf_lo(vw[i]); o[2 * i + 1] = o[2 * i + 1] * a + p * bf_hi(vw[i]); }
  }
  const float m2 = __shfl_xor_sync(0xffffffffu, m, 1), l2 = __shfl_xor_sync(0xffffffffu, l, 1);
  const float mn = fmaxf(m, m2);
  const float a = (m == -INFINITY) ? 0.f : exp2f(m - mn), a2 = (m2 == -INFINITY) ? 0.f : exp2f(m2 - mn);
  const float inv = 1.0f / (l * a + l2 * a2);
#pragma unroll
  for (int i = 0; i < 16; i++) { const float other = __shfl_xor_sync(0xffffffffu, o[i], 1); o[i] = (o[i] * a + other * a2) * inv; }
#pragma unroll
  for (int i = 0; i < 4; i++)
    odst[tile ? (row >> 3) * 64 + par * 32 + (row & 7) * 4 + i : ((row & 7) * 4 + i) * 4 + par * 2 + (row >> 3)] =
        nonzero(par ? pack_bf16(o[8 + 2 * i], o[9 + 2 * i]) : pack_bf16(o[2 * i], o[2 * i + 1]));
}

__device__ __forceinline__ void fma8(float* a, float v, const uint4& w) {
  a[0] = fmaf(v, bf_lo(w.x), a[0]); a[1] = fmaf(v, bf_hi(w.x), a[1]); a[2] = fmaf(v, bf_lo(w.y), a[2]); a[3] = fmaf(v, bf_hi(w.y), a[3]);
  a[4] = fmaf(v, bf_lo(w.z), a[4]); a[5] = fmaf(v, bf_hi(w.z), a[5]); a[6] = fmaf(v, bf_lo(w.w), a[6]); a[7] = fmaf(v, bf_hi(w.w), a[7]);
}

__device__ __forceinline__ void cp16(uint32_t dst, const void* src, bool on) {
  asm volatile("{\n.reg .pred p;\nsetp.ne.u32 p, %2, 0;\n@p cp.async.cg.shared.global [%0], [%1], 16;\n}" :: "r"(dst), "l"(src), "r"((uint32_t)on) : "memory");
}
__device__ __forceinline__ void ffn_cta(int j, uint8_t* sm, const __nv_bfloat16* x, const __nv_bfloat16* wgate,
                                        const __nv_bfloat16* wup, const __nv_bfloat16* wdown) {
  const int tid = threadIdx.x, lane = tid & 31;
  float* xs = (float*)(sm + 196608);
  float* hs = xs + 512;
  float* red = xs + 1024;
  unsigned* ms = (unsigned*)(red + 4096);
  const uint32_t win = (uint32_t)__cvta_generic_to_shared(sm) + tid * 16;
  if (tid == 0) { const unsigned e = __ldcg(&g_epoch[(128 + j) * 8]) + 1u; ms[16] = e; g_epoch[(128 + j) * 8] = e; }
  __syncthreads();
  const unsigned e1 = ms[16];
  const int t4 = min(tid, 447), kg = t4 / 112, r = t4 % 112, mat = r / 56, cg = r % 56;
  const uint4* p1 = (const uint4*)((mat ? wup : wgate) + (size_t)kg * 128 * 1792 + 448 * j + cg * 8);
  const int cg2 = tid & 63, kg2 = tid >> 6;
  const uint4* p2 = (const uint4*)(wdown + (size_t)(448 * j + kg2 * 56) * 512 + cg2 * 8);
#define FFN_ISSUE(G) do { \
    _Pragma("unroll") for (int u = 0; u < 4; u++) { \
      const int k = (G) * 4 + u; \
      cp16(win + (k % 24) * 8192, k < 128 ? p1 + (size_t)k * 224 : p2 + (size_t)(k - 128) * 64, k < 128 ? tid < 448 : k < 184); \
    } \
    asm volatile("cp.async.commit_group;" ::: "memory"); } while (0)
  for (const long long t0 = clock64(); clock64() - t0 < 6000;) __nanosleep(100);
  for (int gi = 0; gi < 6; gi++) FFN_ISSUE(gi);
  unsigned key = 0u;
#pragma unroll
  for (int i = 0; i < 4; i++) {
    uint4 v = ld_rec(&g_rec[tid + 512 * i]);
    wait_rec(v, &g_rec[tid + 512 * i], e1);
    key = max(key, v.z);
  }
  key = __reduce_max_sync(0xffffffffu, key);
  if (lane == 0) ms[tid >> 5] = key;
  __syncthreads();
  key = __reduce_max_sync(0xffffffffu, ms[lane & 15]);
  if (tid < 64) {
    const int idx = (int)(key & 0xFFFFu);
    const uint4 st = ld_rec(&g_rec[idx]);
    const uint4 v = __ldg((const uint4*)(x + (size_t)idx * 512 + tid * 8));
    const uint32_t w[4] = {v.x, v.y, v.z, v.w};
#pragma unroll
    for (int i = 0; i < 4; i++) {
      const uint32_t n = ln_apply(w[i], __uint_as_float(st.x), __uint_as_float(st.y));
      xs[tid * 8 + 2 * i] = bf_lo(n); xs[tid * 8 + 2 * i + 1] = bf_hi(n);
    }
  }
  if (tid == 64 && j == 0) st_tag64(&g_sel, key, e1);
  __syncthreads();
  float a[8] = {0.f, 0.f, 0.f, 0.f, 0.f, 0.f, 0.f, 0.f};
#pragma unroll 1
  for (int gi = 0; gi < 32; gi++) {
    asm volatile("cp.async.wait_group 5;" ::: "memory");
#pragma unroll
    for (int u = 0; u < 4; u++) fma8(a, xs[kg * 128 + gi * 4 + u], lds128(win + ((gi * 4 + u) % 24) * 8192));
    FFN_ISSUE(gi + 6);
  }
  if (tid < 448) {
#pragma unroll
    for (int i = 0; i < 8; i++) red[(kg * 2 + mat) * 448 + cg * 8 + i] = a[i];
  }
  __syncthreads();
  if (tid < 448) {
    const float gv = bf16r(red[tid] + red[896 + tid] + red[1792 + tid] + red[2688 + tid]);
    const float uv = bf16r(red[448 + tid] + red[1344 + tid] + red[2240 + tid] + red[3136 + tid]);
    const float sg = bf16r(gv / (1.0f + expf(-gv)));
    hs[tid] = bf16r(sg * uv);
  }
  __syncthreads();
#pragma unroll
  for (int i = 0; i < 8; i++) a[i] = 0.f;
#pragma unroll 1
  for (int gi = 32; gi < 46; gi++) {
    asm volatile("cp.async.wait_group 5;" ::: "memory");
#pragma unroll
    for (int u = 0; u < 4; u++) fma8(a, hs[kg2 * 56 + (gi - 32) * 4 + u], lds128(win + ((gi * 4 + u) % 24) * 8192));
    FFN_ISSUE(gi + 6);
  }
#pragma unroll
  for (int i = 0; i < 8; i++) red[kg2 * 512 + cg2 * 8 + i] = a[i];
  __syncthreads();
  float y = 0.f;
#pragma unroll
  for (int k = 0; k < 8; k++) y += red[k * 512 + tid];
  st_tag64(&g_y[j * 512 + tid], __float_as_uint(y), e1);
}

__device__ __forceinline__ void make_qa(uint32_t* qa, float m0, float m1, int t) {
  const float h0 = bf16r(m0), h1 = bf16r(m1);
  uint32_t p0 = pack_bf16(h0 * SC_Q, (m0 - h0) * SC_Q);
  const uint32_t p1 = pack_bf16(h1 * SC_Q, (m1 - h1) * SC_Q);
  p0 = (fabsf(m0) + fabsf(m1) < 30000.f) ? p0 : 0x7FC07FC0u;
  const uint32_t dl = (t == 1) ? 0xA2F02717u : (t == 2 ? 0x00002AFEu : 0u);
  qa[0] = (t == 0) ? p0 : dl;
  qa[1] = (t == 0) ? p1 : dl;
}
__device__ __forceinline__ void row_offsets(const float* s, float& m0, float& m1) {
  float a0 = fmaxf(s[0], s[1]), a1 = fmaxf(s[2], s[3]), b0 = fmaxf(s[28], s[29]), b1 = fmaxf(s[30], s[31]);
#pragma unroll
  for (int j = 1; j < 7; j++) {
    if (j < NMUFU / 8) { a0 = fmaxf(a0, fmaxf(s[4 * j], s[4 * j + 1])); a1 = fmaxf(a1, fmaxf(s[4 * j + 2], s[4 * j + 3])); }
    else { b0 = fmaxf(b0, fmaxf(s[4 * j], s[4 * j + 1])); b1 = fmaxf(b1, fmaxf(s[4 * j + 2], s[4 * j + 3])); }
  }
  a0 = fmaxf(a0, __fmul_rn(__fmul_rn(b0, 0x1p71f), 0x1p71f));
  a1 = fmaxf(a1, __fmul_rn(__fmul_rn(b1, 0x1p71f), 0x1p71f));
  a0 = fmaxf(a0, __shfl_xor_sync(0xffffffffu, a0, 1)); a1 = fmaxf(a1, __shfl_xor_sync(0xffffffffu, a1, 1));
  a0 = fmaxf(a0, __shfl_xor_sync(0xffffffffu, a0, 2)); a1 = fmaxf(a1, __shfl_xor_sync(0xffffffffu, a1, 2));
  m0 = -(ceilf(a0) + M_MARGIN);
  m1 = -(ceilf(a1) + M_MARGIN);
}
template <int TILE>
__device__ __forceinline__ void publish_o(const float* o, uint4* odst, const uint8_t* kvh, uint32_t qaddr, uint32_t* qscr) {
  const int lane = threadIdx.x & 31;
  const float l0 = __shfl_sync(0xffffffffu, o[8], lane & 28), l1 = __shfl_sync(0xffffffffu, o[10], lane & 28);
  float r0, r1;
  asm("rcp.approx.ftz.f32 %0, %1;" : "=f"(r0) : "f"(l0));
  asm("rcp.approx.ftz.f32 %0, %1;" : "=f"(r1) : "f"(l1));
  const float c0 = fmaf(o[0], 0.f, o[1] * 0.f) + fmaf(o[2], 0.f, o[3] * 0.f), c1 = fmaf(o[4], 0.f, o[5] * 0.f) + fmaf(o[6], 0.f, o[7] * 0.f);
  const bool ok = (l0 + l1) + (c0 + c1) < 1e36f;
  if (__all_sync(0xffffffffu, ok)) {
    if (TILE) {
      uint32_t* p = (uint32_t*)odst + lane;
      p[0] = pack_bf16(o[0] * r0, o[1] * r0); p[64] = pack_bf16(o[2] * r1, o[3] * r1);
      p[32] = pack_bf16(o[4] * r0, o[5] * r0); p[96] = pack_bf16(o[6] * r1, o[7] * r1);
    } else {
      odst[lane] = make_uint4(nonzero(pack_bf16(o[0] * r0, o[1] * r0)), nonzero(pack_bf16(o[2] * r1, o[3] * r1)),
                              nonzero(pack_bf16(o[4] * r0, o[5] * r0)), nonzero(pack_bf16(o[6] * r1, o[7] * r1)));
    }
  } else {
    const uint4 q = lds128(qaddr);
    attn_fallback(q.x, q.y, q.z, q.w, kvh, (uint32_t*)odst, qscr, TILE);
  }
  __syncwarp();
}

__global__ void __cluster_dims__(2, 1, 1) __launch_bounds__(512, 1)
fused_kernel(const __grid_constant__ CUtensorMap tm_x, const __grid_constant__ CUtensorMap tm_wqkv,
             const __grid_constant__ CUtensorMap tm_wo, const __grid_constant__ CUtensorMap tm_xr,
             const __nv_bfloat16* __restrict__ x, const __nv_bfloat16* __restrict__ wr,
             const __nv_bfloat16* __restrict__ wgate, const __nv_bfloat16* __restrict__ wup,
             const __nv_bfloat16* __restrict__ wdown, __nv_bfloat16* __restrict__ out) {
  extern __shared__ __align__(1024) uint8_t smem[];
  const int b = blockIdx.x;
  if (b >= 128) { ffn_cta(b - 128, smem, x, wgate, wup, wdown); return; }
  const int tid = threadIdx.x, lane = tid & 31;
  const int warp = (int)__reduce_max_sync(0xffffffffu, (unsigned)tid >> 5);
  const int wgi = warp >> 2, wq = warp & 3, hf = wgi & 1, s = wgi >> 1;
  const int g = lane >> 2, t = lane & 3;
  const int rb = b & 15, cb = b >> 4;
  const uint32_t sb = (uint32_t)__cvta_generic_to_shared(smem);
  const uint32_t bar = sb + SM_BAR;
  volatile unsigned* misc = (volatile unsigned*)(smem + SM_MISC);

  const uint32_t ring = sb + s * R_STREAM;
  const uint32_t stash = sb + SM_STASH + tid * 16;
  if (s == 1) {
    const int hw = warp - 8, ht = tid - 256;
    const unsigned ticket = ld_relaxed(&g_epoch[b * 8]) + 1u;
    if (ht >= 64 && ht < 128) {
      const bool km = (ht - 64) < NMUFU;
      sts128(sb + SM_AUG + (ht - 64) * 16, km ? 0x57805780u : 0x10801080u, km ? 0x57805780u : 0u, km ? 0u : 0x00001080u, 0u);
    }
    if (ht == 160) {
      asm volatile("prefetch.tensormap [%0];" :: "l"(&tm_wo) : "memory");
      asm volatile("prefetch.tensormap [%0];" :: "l"(&tm_xr) : "memory");
    }
    if (ht == 128) sts128(sb + SM_MISC + 80, 0x3F003F00u, 0x00010001u, 0u, 0u);
    if (lane == 0) {
#pragma unroll
      for (int i = 0; i < 12; i++) mbar_init(sb + SM_RBAR + 96 * hw + 8 * i, (hw & 3) == 1 ? (i ? 2 : 3) : ((hw & 3) == 0 && i == 11 ? 3 : 1));
      asm volatile("fence.mbarrier_init.release.cluster;" ::: "memory");
    }
    bar_sync(0, 512);
    mbar_wait(bar + B_S, 0);
    const uint32_t xs = sb + 2 * A_STAGE + hw * 2048 + lane * 16;
    const uint4 wa = lds128(sb + SM_RED + RED_WR + lane * 16), wb = lds128(sb + SM_RED + RED_WR + 512 + lane * 16);
    const uint4 xa = lds128(xs), xb = lds128(xs + 512), xc = lds128(xs + 1024), xd = lds128(xs + 1536);
    if (lane < 24) {
      const int kr = (rb & 1) * 32 + hw * 4;
      const uint32_t ws = sb + 2 * A_STAGE + A_WOFF + (lane >> 3) * 8192 + kr * 128;
      const uint4 c0 = lds128(ws + (((lane & 7) ^ (kr & 7)) << 4)), c1 = lds128(ws + 128 + (((lane & 7) ^ ((kr + 1) & 7)) << 4));
      const uint4 c2 = lds128(ws + 256 + (((lane & 7) ^ ((kr + 2) & 7)) << 4)), c3 = lds128(ws + 384 + (((lane & 7) ^ ((kr + 3) & 7)) << 4));
      const uint32_t a = sb + SM_RED + hw * 768 + lane * 32;
      sts128(a, __float_as_uint((bf_lo(c0.x) + bf_lo(c1.x)) + (bf_lo(c2.x) + bf_lo(c3.x))), __float_as_uint((bf_hi(c0.x) + bf_hi(c1.x)) + (bf_hi(c2.x) + bf_hi(c3.x))),
                __float_as_uint((bf_lo(c0.y) + bf_lo(c1.y)) + (bf_lo(c2.y) + bf_lo(c3.y))), __float_as_uint((bf_hi(c0.y) + bf_hi(c1.y)) + (bf_hi(c2.y) + bf_hi(c3.y))));
      sts128(a + 16, __float_as_uint((bf_lo(c0.z) + bf_lo(c1.z)) + (bf_lo(c2.z) + bf_lo(c3.z))), __float_as_uint((bf_hi(c0.z) + bf_hi(c1.z)) + (bf_hi(c2.z) + bf_hi(c3.z))),
                     __float_as_uint((bf_lo(c0.w) + bf_lo(c1.w)) + (bf_lo(c2.w) + bf_lo(c3.w))), __float_as_uint((bf_hi(c0.w) + bf_hi(c1.w)) + (bf_hi(c2.w) + bf_hi(c3.w))));
    }
    __syncwarp();
    if (hw == 7) {
      bar_sync(4, 256);
      elect_load_ax(sb + 2 * A_STAGE, &tm_wqkv, &tm_x, 64 * 6, 64 * cb, rb * 128, bar + B_FULLA + 48);
    } else {
      bar_arrive(4, 256);
    }
    {
      const uint32_t ww[8] = {wa.x, wa.y, wa.z, wa.w, wb.x, wb.y, wb.z, wb.w};
      float w[16], v[8];
      v[3] = 0.f;
#pragma unroll
      for (int i = 0; i < 8; i++) { w[2 * i] = bf_lo(ww[i]); w[2 * i + 1] = bf_hi(ww[i]); v[3] += w[2 * i] + w[2 * i + 1]; }
      ln_partial(xa, xb, w, v);
      ln_partial(xc, xd, w, v + 4);
      v[7] = v[3];
      const float tot = warp_sum8(v, lane);
      if (t == 0) sts32(sb + SM_RED + RED_REC + hw * 32 + g * 4, __float_as_uint(tot));
    }
    if (ht == 0) misc[16] = ticket;
    bar_sync(6, 256);
    const unsigned e = misc[16];
    if (hw < 2) {
      const float* rp = (const float*)(smem + SM_RED) + ht * 3;
      float v0 = 0.f, v1 = 0.f, v2 = 0.f;
#pragma unroll
      for (int i = 0; i < 8; i++) { v0 += rp[i * 192]; v1 += rp[i * 192 + 1]; v2 += rp[i * 192 + 2]; }
      st_rec(&g_cs[(cb * 16 + rb) * 64 + ht], __float_as_uint(v0), __float_as_uint(v1), __float_as_uint(v2), e);
    } else if (ht < 80) {
      const int r = ht - 64;
      const uint4 v = lds128(sb + SM_RED + RED_REC + r * 16);
      const float md = __uint_as_float(v.x) * (1.0f / 512.0f);
      const float mb = bf16r(md);
      const float rs = 1.0f / bf16r(sqrtf(bf16r(bf16r(fmaxf(fmaf(-md, md, __uint_as_float(v.y) * (1.0f / 512.0f)), 0.f)) + 1e-5f)));
      const float rv = fmaf(-mb, __uint_as_float(v.w), __uint_as_float(v.z)) * rs;
      uint32_t rbits = pack_bf16(rv + 0.0f, 0.f) & 0xFFFFu;
      rbits = (rbits & 0x8000u) ? (~rbits & 0xFFFFu) : (rbits | 0x8000u);
      if (rv != rv) rbits = 0u;
      const int row = rb * 128 + cb * 16 + r;
      st_rec(&g_rec[row], __float_as_uint(mb), __float_as_uint(rs), (rbits << 16) | (uint32_t)row, e);
    } else if (ht == 96) {
      g_epoch[b * 8] = ticket;
    }
    __syncwarp();
    mbar_wait(bar + B_FULLA + 56, 0);
    if (hw < 2) {
      uint32_t gs[64];
      wait_cs(gs, &g_cs[cb * 1024 + ht], e);
      float v0 = 0.f, v1 = 0.f, v2 = 0.f;
#pragma unroll
      for (int i = 0; i < 16; i++) { v0 += __uint_as_float(gs[4 * i]); v1 += __uint_as_float(gs[4 * i + 1]); v2 += __uint_as_float(gs[4 * i + 2]); }
      const float h0 = bf16r(v0), h1 = bf16r(v1), h2 = bf16r(v2);
      sts128(sb + SM_RED + RED_CS + ht * 48, pack_bf16(h0, v0 - h0), 0u, 0u, 0u);
      sts128(sb + SM_RED + RED_CS + ht * 48 + 16, pack_bf16(h1, v1 - h1), 0u, 0u, 0u);
      sts128(sb + SM_RED + RED_CS + ht * 48 + 32, pack_bf16(h2, v2 - h2), 0u, 0u, 0u);
      fence_async_smem();
    } else if (hw < 6) {
      uint4 v = ld_rec(&g_rec[rb * 128 + ht - 64]);
      wait_rec(v, &g_rec[rb * 128 + ht - 64], e);
      ((float2*)(smem + SM_STAT))[ht - 64] = make_float2(__uint_as_float(v.x), __uint_as_float(v.y));
    }
    bar_arrive(2, 512);
    bar_sync(1, 512);
    asm volatile("barrier.cluster.arrive.relaxed.aligned;" ::: "memory");
    if (warp == 14) arrive_if(sb + SM_RBAR + 384 * (lane & 1) + 80, lane < 2);
#pragma unroll
    for (int i = 0; i < 6; i++) sts128(sb + ((ht >> 7) + 2 * i) * R_SLOT + 8192 + (ht & 127) * 16, 0x00003F80u, 0u, 0u, 0u);
    fence_async_smem();
    bar_arrive(3, 512);
    bar_sync(5, 512);
  } else {
    if (warp == 0) {
      if (lane == 0) {
        mbar_init(bar, 1);
        asm volatile("fence.mbarrier_init.release.cluster;" ::: "memory");
      }
      __syncwarp();
      elect_load_ax(sb, &tm_wqkv, &tm_x, 0, 64 * cb, rb * 128, bar + B_FULLA);
      if (lane == 0) {
#pragma unroll
        for (int i = 1; i < 14; i++) mbar_init(bar + 8 * i, (i >= 8 && i < 12) ? 2 : 1);
        asm volatile("fence.mbarrier_init.release.cluster;" ::: "memory");
      }
      __syncwarp();
    }
    bar_sync(0, 512);
    if (warp == 0) {
      elect_load_ax(sb + A_STAGE, &tm_wqkv, &tm_x, 64, 64 * cb, rb * 128, bar + B_FULLA + 8);
      elect_load_stats(sb + 2 * A_STAGE, &tm_wqkv, 64 * (rb >> 1), 64 * cb, x + (size_t)(rb * 128 + cb * 16) * 512, sb + SM_RED + RED_WR, wr, bar + B_S);
      elect_load_ax(sb + 3 * A_STAGE, &tm_wqkv, &tm_x, 128, 64 * cb, rb * 128, bar + B_FULLA + 16);
      elect_load_ax(sb + 4 * A_STAGE, &tm_wqkv, &tm_x, 192, 64 * cb, rb * 128, bar + B_FULLA + 24);
    }
    float acc[96];
#pragma unroll
    for (int i = 0; i < 96; i++) acc[i] = 0.f;
#pragma unroll
    for (int j = 0; j < 8; j++) {
      const int sl = (j < 2) ? j : (j < 4 ? j + 1 : j - 4);
      mbar_wait(bar + B_FULLA + 8 * j, 0);
      uint64_t da = mkdesc(sb + sl * A_STAGE + hf * 8192, 16, 1024, 1);
      uint64_t db = mkdesc(sb + sl * A_STAGE + A_WOFF, 8192, 1024, 1);
      wg_fence();
#pragma unroll
      for (int kk = 0; kk < 4; kk++) { wg_ss_n192_t(acc, da, db, 1); DESC_ADD(da, 2); DESC_ADD(db, 128); }
      wg_commit();
      if (j >= 1 && j <= 3) {
        wg_wait<1>();
        arrive_if(bar + B_EMPTYA + 8 * (j - 1), (tid & 127) == 0);
        if (warp == 4) {
          const int sp = (j == 3) ? 3 : j - 1;
          mbar_wait(bar + B_EMPTYA + 8 * (j - 1), 0);
          elect_load_ax(sb + sp * A_STAGE, &tm_wqkv, &tm_x, 64 * (sp + 4), 64 * cb, rb * 128, bar + B_FULLA + 8 * (sp + 4));
        }
      }
    }
    bar_sync(2, 512);
    const float2 st0 = ((const float2*)(smem + SM_STAT))[hf * 64 + wq * 16 + g];
    const float2 st1 = ((const float2*)(smem + SM_STAT))[hf * 64 + wq * 16 + g + 8];
    {
      uint32_t am[4] = {t ? 0u : pack_bf16(-st0.x, -st0.x), t ? 0u : pack_bf16(-st1.x, -st1.x), 0u, 0u};
      PIN_R(am[0]); PIN_R(am[1]); PIN_R(am[2]); PIN_R(am[3]);
      wg_fence();
      wg_rs_n192(acc, am, mkdesc(sb + SM_RED + RED_CS, 0, 128, 0), 1);
      wg_commit();
    }
    wg_wait<0>();
    PIN_ACC96;
    uint32_t f[48];
    const float k0 = (((KPERM >> (8 * wq)) & 7) < NMUFU / 8) ? SC_KM : SC_KP, k1 = (((KPERM >> (8 * wq + 4)) & 7) < NMUFU / 8) ? SC_KM : SC_KP;
#pragma unroll
    for (int j = 0; j < 24; j++) {
      const float qs = 0.25f * 1.4426950408889634f * SC_Q;
      const float r0 = st0.y * (j < 8 ? qs : (j < 16 ? k0 : 1.0f)), r1 = st1.y * (j < 8 ? qs : (j < 16 ? k1 : 1.0f));
      f[2 * j] = pack_bf16(acc[4 * j] * r0, acc[4 * j + 1] * r0);
      f[2 * j + 1] = pack_bf16(acc[4 * j + 2] * r1, acc[4 * j + 3] * r1);
    }
    const int mi = lane >> 3, i8 = 2 * wq + (mi & 1);
    const uint32_t ko = sb + hf * 2048 + ((KPERM >> (4 * i8)) & 7) * 256 + (mi >> 1) * 128 + (lane & 7) * 16;
    const uint32_t vo = sb + 4096 + (mi >> 1) * 2048 + (hf * 8 + i8) * 128 + (lane & 7) * 16;
    bar_sync(1, 512);
    asm volatile("barrier.cluster.arrive.relaxed.aligned;" ::: "memory");
#pragma unroll
    for (int h = 3; h >= 0; h--) {
      const uint32_t so = (h >> 1) * R_STREAM + (3 + ((h & 1) ^ 1)) * R_SLOT;
      stsm4(ko + so, f[16 + 4 * h], f[17 + 4 * h], f[18 + 4 * h], f[19 + 4 * h]);
      stsm4(vo + so, f[32 + 4 * h], f[33 + 4 * h], f[34 + 4 * h], f[35 + 4 * h]);
      sts128(stash + (h >> 1) * 4096 + ((h & 1) ^ 1) * 16384, f[4 * h], f[4 * h + 1], f[4 * h + 2], f[4 * h + 3]);
      if (h == 2) { fence_async_smem(); bar_arrive(5, 512); }
    }
    fence_async_smem();
    bar_sync(3, 512);
  }
  const uint8_t* kvs = g_kv + (cb * 4 + s * 2) * 131072;
  const uint32_t bfull = sb + SM_RBAR + 384 * s;
  if (wq == 0 && hf == 1)
    asm volatile("{\n.reg .pred p;\n.reg .u32 rd, rb;\nelect.sync _|p, 0xffffffff;\n"
                 "mapa.shared::cluster.u32 rd, %4, %6;\nmapa.shared::cluster.u32 rb, %5, %6;\n"
                 "@p cp.async.bulk.global.shared::cta.bulk_group [%0], [%1], 8192;\n"
                 "@p cp.async.bulk.global.shared::cta.bulk_group [%2], [%3], 8192;\n"
                 "@p cp.async.bulk.commit_group;\nbarrier.cluster.wait.aligned;\n"
                 "@p cp.async.bulk.shared::cluster.shared::cta.mbarrier::complete_tx::bytes [rd], [%1], 8192, [rb];\n"
                 "@p mbarrier.arrive.expect_tx.shared::cta.b64 _, [%5], 8192;\n}"
                 :: "l"(kvs + rb * 8192), "r"(ring + 4 * R_SLOT), "l"(kvs + 131072 + rb * 8192), "r"(ring + 3 * R_SLOT),
                    "r"(ring), "r"(bfull), "r"((b & 1) ^ 1) : "memory");
  const int dir = 1 - 2 * (rb & 1);
  const unsigned e1 = __reduce_max_sync(0xffffffffu, misc[16]);

  const uint64_t daug = mkdesc(sb + SM_AUG, 0, 128, 0);
  const uint64_t dk0 = mkdesc(ring, 128, 256, 0);
  const uint64_t dv0 = mkdesc(ring + 4096, 128, 2048, 0);
  const bool loader = (hf == 1) && (wq == 0);
  const uint32_t is_t0 = (tid & 127) == 0;
  const uint4 kc = lds128(sb + SM_MISC + 80);
  const uint32_t kmant = kc.x, kexpo = kc.y;
  const uint4* const osrc = g_o + ((b >> 3) * 32 + s * 16) * 256;
  uint4* const obase = g_o + (rb * 32 + s * 16 + cb) * 256 + hf * 128 + wq * 32;
  uint32_t* const qscr = g_qscr + (b * 16 + warp) * 128;
  {
    float s0[32], s1[32], o[12];
    uint32_t pr[16], qa[4], qf[4], qo[4];
    {
      const uint4 v = lds128(stash), w = lds128(stash + 16384);
      qf[0] = v.x; qf[1] = v.y; qf[2] = v.z; qf[3] = v.w;
      qo[0] = w.x; qo[1] = w.y; qo[2] = w.z; qo[3] = w.w;
    }
#pragma unroll
    for (int i = 0; i < 32; i++) { s0[i] = 0.f; s1[i] = 0.f; }
#pragma unroll
    for (int i = 0; i < 12; i++) o[i] = 0.f;
    uint64_t dkt = dk0 + 3 * (R_SLOT / 16), dvt = dv0 + 3 * (R_SLOT / 16);
    PIN_S0; PIN_S1; PIN_O;
    wg_fence();
    wg_rs_n64(s0, qf, dkt, 0);
    wg_rs_n64(s1, qo, dkt + R_SLOT / 16, 0);
    DESC_ADD(dkt, 128);
    wg_commit();
    wg_wait<0>();
    PIN_S0; PIN_S1;
    {
      float m0, m1, n0, n1;
      row_offsets(s0, m0, m1);
      row_offsets(s1, n0, n1);
      sts128(stash + 8192, __float_as_uint(m0), __float_as_uint(m1), __float_as_uint(n0), __float_as_uint(n1));
      make_qa(qa, m0, m1, t);
      qa[2] = kc.z; qa[3] = kc.w;
      PIN_QA;
      wg_fence();
      wg_rs_n64(s0, qa, daug, 1);
      wg_commit();
    }
    if (loader) {
      asm volatile("{\n.reg .pred p;\nelect.sync _|p, 0xffffffff;\n@p cp.async.bulk.wait_group 0;\n}" ::: "memory");
      __syncwarp();
      if (lane < 2) st_rec(&g_flag[b * 4 + s * 2 + lane], e1 - 1u, e1, 0u, 0u);
      __syncwarp();
    }
    wg_wait<0>();
    const unsigned* const kflag = &g_flag[(cb * 16 + (lane & 15)) * 4 + s * 2].y;
    unsigned kfl = 0u;
#pragma unroll 1
    for (int loc = 0; loc < 2; loc++) {
      PIN_S0; PIN_O;
      TILE_S0();
      if (loc) {
        mbar_wait(bfull, 0);
        if (loader) {
          wait_flag_warp(kflag, e1, kfl);
          elect_load2(ring + R_SLOT, kvs + ((rb + 2 * dir) & 15) * 8192, ring + 2 * R_SLOT, kvs + ((rb + 3 * dir) & 15) * 8192, 8192, bfull + 192, 16384);
        }
        if (loader)
          asm volatile("{\n.reg .pred p;\n.reg .u32 r;\nelect.sync _|p, 0xffffffff;\nmapa.shared::cluster.u32 r, %0, %1;\n"
                       "@p mbarrier.arrive.relaxed.cluster.shared::cluster.b64 _, [r];\n}" :: "r"(bfull + 96), "r"((b & 1) ^ 1) : "memory");
      }
      wg_wait<0>();
      PIN_S1; PIN_O;
      dkt = dk0;
      TILE_S1();
      wg_wait<0>();
      PIN_S0; PIN_O;
      if (loc) break;
      const uint4 q = lds128(stash + 16384), m = lds128(stash + 8192);
      qf[0] = q.x; qf[1] = q.y; qf[2] = q.z; qf[3] = q.w;
      make_qa(qa, __uint_as_float(m.z), __uint_as_float(m.w), t);
      PIN_QA;
      dkt = dk0 + 4 * (R_SLOT / 16);
      dvt = dv0 + 4 * (R_SLOT / 16);
      QK_S0;
      if (loader) kfl = ld_relaxed(kflag);
      obase[2048 + lane] = make_uint4(0u, 0u, 0u, 0u);
      sts128(stash + 8192, m.x, m.y, __float_as_uint(o[8]), __float_as_uint(o[10]));
      sts128(stash + 24576, __float_as_uint(o[0]), __float_as_uint(o[1]), __float_as_uint(o[2]), __float_as_uint(o[3]));
      sts128(stash + 32768, __float_as_uint(o[4]), __float_as_uint(o[5]), __float_as_uint(o[6]), __float_as_uint(o[7]));
#pragma unroll
      for (int i = 0; i < 12; i++) o[i] = 0.f;
      wg_wait<0>();
    }
    if (!loader) asm volatile("barrier.cluster.wait.aligned;" ::: "memory");
    arrive_if(bfull + 96, is_t0);
    dvt = dv0;
    uint64_t jk = 1920 - 1536, jv = 1920 - 1408;
    uint32_t bst = bfull, cfl = 0u;
    const unsigned* const cflag = &g_flag[((lane & 7) * 16 + (b >> 3)) * 4 + s * 2].x;
    uint32_t lturn = (wq == 0) ? (hf ? 0x355u : 0x0ABu) : 1u;
#pragma unroll 1
    for (int seg = 0; seg < 2; seg++) {
#pragma unroll 1
      for (int it = 0; it < 5; it++) {
        uint32_t oke, okf;
        PIN_S0; PIN_O;
        TILE_S0(oke = mbar_test(bst + 96, 0));
        if (lturn & 1) {
          const int st = seg * 5 + it;
          if (st == 0) mbar_wait(bfull + 192, 0);
          if (st || loader) {
            mbar_wait_if_not(oke, bst + 96, 0);
            const uint32_t dst = ring + ((st & 1) ^ 1) * 3 * R_SLOT;
            if (st < 9) {
              const int h = (st >= 4), u = rb + dir * (4 + 3 * st + h);
              const uint8_t* hb = kvs + h * 131072;
              elect_load3(dst, hb + (u & 15) * 8192, hb + ((u + dir) & 15) * 8192, hb + ((u + 2 * dir) & 15) * 8192, bst + 8);
              if (st == 8) cfl = ld_relaxed(cflag);
              if (st == 1) elect_tma2d(sb + SM_WO + s * 32768, &tm_wo, 64 * (b & 7), 256 * s, bar + B_WO, 32768);
              if (st == 6) {
                __threadfence();
                if (lane < 2) st_rec(&g_flag[b * 4 + s * 2 + lane], e1, e1, 0u, 0u);
                __syncwarp();
              }
            } else {
              const uint32_t dp = sb + SM_STASH + 16384 + s * 4096;
              wait_flag_warp(cflag, e1, cfl);
              elect_load2v(dst, osrc, 28672, dp, osrc + 7 * 256, 4096, bst + 16);
              elect_load(dst + 28672, &g_rec[(b >> 3) * 128], 2048, bst + 16);
              elect_tma2d(dp + 8192, &tm_xr, (b & 7) * 64 + s * 32, (b >> 3) * 128, bst + 16, 8192);
              elect_tma2d(dp + 16384, &tm_xr, (b & 7) * 64 + s * 32, (b >> 3) * 128 + 64, bst + 16, 0);
            }
          }
        }
        wg_wait<0>();
        PIN_S1; PIN_O;
        DESC_ADD(dkt, 384);
        TILE_S1();
        wg_wait<0>();
        PIN_S0; PIN_O;
        DESC_ADD(dvt, 512);
        TILE_S0();
        wg_wait<0>();
        PIN_S1; PIN_O;
        DESC_ADD(dkt, 384);
        TILE_S1();
        wg_wait<0>();
        PIN_S0; PIN_O;
        DESC_ADD(dvt, 512);
        TILE_S0(okf = mbar_test(bst + 8, 0));
        mbar_wait_if_not(okf, bst + 8, 0);
        wg_wait<0>();
        PIN_S1; PIN_O;
        asm volatile("add.s64 %0, %0, %1;\nsub.s64 %1, -3072, %1;" : "+l"(dkt), "+l"(jk));
        TILE_S1();
        wg_wait<0>();
        asm volatile("add.s64 %0, %0, %1;\nsub.s64 %1, -2816, %1;" : "+l"(dvt), "+l"(jv));
        arrive_if(bst + 104, is_t0);
        bst += 8;
        lturn >>= 1;
      }
      PIN_S0; PIN_O;
      if (seg) break;
      const uint4 q = lds128(stash), m = lds128(stash + 8192);
      qf[0] = q.x; qf[1] = q.y; qf[2] = q.z; qf[3] = q.w;
      make_qa(qa, __uint_as_float(m.x), __uint_as_float(m.y), t);
      PIN_QA;
      publish_o<1>(o, obase, kvs, stash + 16384, qscr);
      const uint4 v0 = lds128(stash + 24576), v1 = lds128(stash + 32768);
      o[0] = __uint_as_float(v0.x); o[1] = __uint_as_float(v0.y); o[2] = __uint_as_float(v0.z); o[3] = __uint_as_float(v0.w);
      o[4] = __uint_as_float(v1.x); o[5] = __uint_as_float(v1.y); o[6] = __uint_as_float(v1.z); o[7] = __uint_as_float(v1.w);
      o[8] = __uint_as_float(m.z); o[9] = 0.f; o[10] = __uint_as_float(m.w); o[11] = 0.f;
      fence_async_smem();
      PIN_O;
      DESC_ADD(dkt, -128);
      QK_S0;
      wg_wait<0>();
    }
    publish_o<0>(o, obase + 2048, kvs + 131072, stash, qscr);
  }

  {
    const int rc = b >> 3, cc = b & 7;
    const int row0 = rc * 128 + hf * 64 + wq * 16 + g;
    const uint4* op = osrc + hf * 128 + (tid & 127);
    uint32_t af[32];
    float acc2[32];
#pragma unroll
    for (int i = 0; i < 32; i++) acc2[i] = 0.f;
    mbar_wait(bfull + 88, 0);
    mbar_wait(bar + B_WO, 0);
    uint64_t db = mkdesc(sb + SM_WO + s * 4096, 16, 1024, 1);
    {
      uint64_t da = mkdesc(ring + hf * 2048, 128, 256, 0);
      PIN_ACC32;
      wg_fence();
#pragma unroll
      for (int c = 0; c < 7; c++) { wg_ss_n64_t(acc2, da, db, 1); DESC_ADD(da, 256); DESC_ADD(db, 512); }
      wg_ss_n64_t(acc2, mkdesc(sb + SM_STASH + 16384 + s * 4096 + hf * 2048, 128, 256, 0), db, 1);
      wg_commit();
      DESC_ADD(db, -3456);
    }
#pragma unroll
    for (int c = 0; c < 8; c++) ld_frag(af + 4 * c, op + c * 256 + 2048);
    uint2 sel2 = ld_tag64(&g_sel);
    float res[16];
    {
      const int rl = hf * 64 + wq * 16 + g;
      const uint4 st0 = lds128(ring + 28672 + rl * 16), st1 = lds128(ring + 28672 + rl * 16 + 128);
      uint32_t xv[8];
#pragma unroll
      for (int i = 0; i < 8; i++)
        xv[i] = lds32(sb + SM_STASH + 24576 + hf * 8192 + s * 4096 + (wq * 16 + g + 8 * (i & 1)) * 64 + (((i >> 1) ^ ((g >> 1) & 3)) << 4) + t * 4);
#pragma unroll
      for (int i = 0; i < 8; i++) {
        const uint32_t nn = ln_apply(xv[i], __uint_as_float((i & 1) ? st1.x : st0.x), __uint_as_float((i & 1) ? st1.y : st0.y));
        res[2 * i] = bf_lo(xv[i]) + bf_lo(nn);
        res[2 * i + 1] = bf_hi(xv[i]) + bf_hi(nn);
      }
    }
    const unsigned key = wait_tag64(sel2, &g_sel, e1);
    const int sel = (int)(key & 0xFFFFu);
    const bool routed = (sel >> 4) == (row0 >> 4);
    const unsigned long long* yp = g_y + cc * 64 + s * 32 + lane;
    uint2 y0 = make_uint2(0u, 0u), y1 = y0, y2 = y0, y3 = y0;
    float sg = 0.f;
    if (routed) {
      y0 = ld_tag64(yp); y1 = ld_tag64(yp + 512); y2 = ld_tag64(yp + 1024); y3 = ld_tag64(yp + 1536);
      const uint32_t rk = key >> 16;
      const float rv = __uint_as_float(((rk & 0x8000u) ? (rk & 0x7FFFu) : (~rk & 0xFFFFu)) << 16);
      sg = bf16r(1.0f / (1.0f + expf(-rv)));
      PIN_F(sg);
    }
    __syncwarp();
#pragma unroll
    for (int c2 = 0; c2 < 8; c2 += 4) {
      if (c2 == 0) wait_frags8_4(af, op + 2048);
      else wait_frags4_4(af + 16, op + 2048 + 1024);
      wg_fence();
#pragma unroll
      for (int c = c2; c < c2 + 4; c++) { wg_rs_n64_t(acc2, af + 4 * c, db, 1); DESC_ADD(db, 512); }
      wg_commit();
    }
    const uint32_t xslot = ring + (tid & 255) * 16;
    wg_wait<0>();
    PIN_ACC32;
    float r[16];
#pragma unroll
    for (int i = 0; i < 16; i++) r[i] = s ? acc2[16 + i] : acc2[i];
#pragma unroll
    for (int i = 0; i < 4; i++)
      sts128(i < 3 ? stash + i * 8192 : xslot, __float_as_uint(s ? acc2[4 * i] : acc2[16 + 4 * i]), __float_as_uint(s ? acc2[4 * i + 1] : acc2[17 + 4 * i]),
             __float_as_uint(s ? acc2[4 * i + 2] : acc2[18 + 4 * i]), __float_as_uint(s ? acc2[4 * i + 3] : acc2[19 + 4 * i]));
    if (hf) bar_sync(6, 256); else bar_sync(4, 256);
#pragma unroll
    for (int i = 0; i < 4; i++) {
      const uint4 v = lds128(i < 3 ? sb + SM_STASH + (tid ^ 256) * 16 + i * 8192 : sb + (s ^ 1) * R_STREAM + (tid & 255) * 16);
      r[4 * i] += res[4 * i] + __uint_as_float(v.x); r[4 * i + 1] += res[4 * i + 1] + __uint_as_float(v.y);
      r[4 * i + 2] += res[4 * i + 2] + __uint_as_float(v.z); r[4 * i + 3] += res[4 * i + 3] + __uint_as_float(v.w);
    }
    if (routed) {
      float y = __uint_as_float(wait_tag64(y0, yp, e1));
      y += __uint_as_float(wait_tag64(y1, yp + 512, e1));
      y += __uint_as_float(wait_tag64(y2, yp + 1024, e1));
      y += __uint_as_float(wait_tag64(y3, yp + 1536, e1));
      y = bf16r(bf16r(y) * sg);
#pragma unroll
      for (int j = 0; j < 4; j++) {
#pragma unroll
        for (int c = 0; c < 2; c++) {
          const float v = __shfl_sync(0xffffffffu, y, 8 * j + 2 * t + c);
          r[4 * j + c] += (sel == row0) ? v : 0.f;
          r[4 * j + 2 + c] += (sel == row0 + 8) ? v : 0.f;
        }
      }
    }
    const uint32_t tb = ring + 4096 + (warp & 7) * 512;
    uint4* const orow = (uint4*)(out + (size_t)row0 * 512 + cc * 64 + s * 32) + t;
#pragma unroll
    for (int u = 0; u < 2; u++) {
      stsm4(tb + (lane & 7) * 64 + (((lane >> 3) ^ ((lane >> 1) & 3)) << 4), pack_bf16(r[2 * u], r[2 * u + 1]), pack_bf16(r[4 + 2 * u], r[5 + 2 * u]),
            pack_bf16(r[8 + 2 * u], r[9 + 2 * u]), pack_bf16(r[12 + 2 * u], r[13 + 2 * u]));
      __syncwarp();
      orow[u * 512] = lds128(tb + g * 64 + ((t ^ ((g >> 1) & 3)) << 4));
      __syncwarp();
    }
  }
}

typedef CUresult (*EncodeFn)(CUtensorMap*, CUtensorMapDataType, cuuint32_t, void*, const cuuint64_t*, const cuuint64_t*,
                             const cuuint32_t*, const cuuint32_t*, CUtensorMapInterleave, CUtensorMapSwizzle,
                             CUtensorMapL2promotion, CUtensorMapFloatOOBfill);

}

extern "C" void kernel_launch(void* const* d_in, const int* in_sizes, int n_in, void* d_out, int out_size) {
  (void)in_sizes; (void)n_in; (void)out_size;
  static EncodeFn encode = nullptr;
  if (!encode) {
    void* fn = nullptr;
    cudaDriverEntryPointQueryResult qr;
    cudaGetDriverEntryPoint("cuTensorMapEncodeTiled", &fn, cudaEnableDefault, &qr);
    encode = (EncodeFn)fn;
    cudaFuncSetAttribute(fused_kernel, cudaFuncAttributeMaxDynamicSharedMemorySize, SM_TOTAL);
  }
  CUtensorMap tm_x, tm_wqkv, tm_wo, tm_xr;
  const cuuint32_t es[4] = {1, 1, 1, 1};
  {
    const cuuint64_t dims[2] = {512, 2048};
    const cuuint64_t strides[1] = {1024};
    const cuuint32_t box[2] = {64, 128};
    encode(&tm_x, CU_TENSOR_MAP_DATA_TYPE_BFLOAT16, 2, d_in[0], dims, strides, box, es, CU_TENSOR_MAP_INTERLEAVE_NONE,
           CU_TENSOR_MAP_SWIZZLE_128B, CU_TENSOR_MAP_L2_PROMOTION_L2_128B, CU_TENSOR_MAP_FLOAT_OOB_FILL_NONE);
    const cuuint32_t box2[2] = {32, 64};
    encode(&tm_xr, CU_TENSOR_MAP_DATA_TYPE_BFLOAT16, 2, d_in[0], dims, strides, box2, es, CU_TENSOR_MAP_INTERLEAVE_NONE,
           CU_TENSOR_MAP_SWIZZLE_64B, CU_TENSOR_MAP_L2_PROMOTION_L2_128B, CU_TENSOR_MAP_FLOAT_OOB_FILL_NONE);
  }
  {
    const cuuint64_t dims[3] = {512, 512, 3};
    const cuuint64_t strides[2] = {3072, 1024};
    const cuuint32_t box[3] = {64, 64, 3};
    encode(&tm_wqkv, CU_TENSOR_MAP_DATA_TYPE_BFLOAT16, 3, d_in[1], dims, strides, box, es, CU_TENSOR_MAP_INTERLEAVE_NONE,
           CU_TENSOR_MAP_SWIZZLE_128B, CU_TENSOR_MAP_L2_PROMOTION_L2_128B, CU_TENSOR_MAP_FLOAT_OOB_FILL_NONE);
  }
  {
    const cuuint64_t dims[2] = {512, 512};
    const cuuint64_t strides[1] = {1024};
    const cuuint32_t box[2] = {64, 256};
    encode(&tm_wo, CU_TENSOR_MAP_DATA_TYPE_BFLOAT16, 2, d_in[2], dims, strides, box, es, CU_TENSOR_MAP_INTERLEAVE_NONE,
           CU_TENSOR_MAP_SWIZZLE_128B, CU_TENSOR_MAP_L2_PROMOTION_L2_128B, CU_TENSOR_MAP_FLOAT_OOB_FILL_NONE);
  }
  fused_kernel<<<NCTA, 512, SM_TOTAL>>>(tm_x, tm_wqkv, tm_wo, tm_xr, (const __nv_bfloat16*)d_in[0],
                                        (const __nv_bfloat16*)d_in[4], (const __nv_bfloat16*)d_in[5],
                                        (const __nv_bfloat16*)d_in[6], (const __nv_bfloat16*)d_in[7], (__nv_bfloat16*)d_out);
}
```
